```python
import torch

def _softmax(x, axis=-1):
    return torch.softmax(x, dim=axis)

def _gelu(x):
    return torch.nn.functional.gelu(x, approximate='tanh')

def _silu(x):
    return torch.nn.functional.silu(x)

def _sigmoid(x):
    return torch.sigmoid(x)

def _layernorm(x, axis=-1, eps=1e-05):
    m = x.mean(dim=axis, keepdim=True)
    v = x.var(dim=axis, keepdim=True, unbiased=False)
    return (x - m) / torch.sqrt(v + eps)

def _scatter_add(tgt, idx, src, axis=0):
    return tgt.clone().index_add_(axis, idx, src)

def _segment_sum(src, seg, n):
    out = torch.zeros((n,) + src.shape[1:], dtype=src.dtype)
    return out.index_add_(0, seg, src)

def _pad(x, pw):
    flat = tuple((v for pair in reversed(pw) for v in pair))
    return torch.nn.functional.pad(x, flat)
kernel_name = 'adaLN_cond__sliding_local_dilated__moe_arch_mod__prompt'

def setup_inputs():

    _w = lambda a: (lambda t: t.to(torch.bfloat16) if t.is_floating_point() else t)(torch.as_tensor(a))

    def _A_setup():
        B, S, D = (1, 2048, 640)
        return {'x': _w((lambda *s: torch.randn(*s, dtype=torch.bfloat16) * 0.05)(B, S, D)), 'wqkv': _w((lambda *s: torch.randn(*s, dtype=torch.bfloat16) * 0.05)(D, 3 * D)), 'wo': _w((lambda *s: torch.randn(*s, dtype=torch.bfloat16) * 0.05)(D, D))}
    _A_in = _A_setup()

    def _B_setup():
        B, S, D, F, C = (1, 2048, 640, 1728, 1)
        return {'x': _w((lambda *s: torch.randn(*s, dtype=torch.bfloat16) * 0.05)(B, S, D)), 'w_r': _w((lambda *s: torch.randn(*s, dtype=torch.bfloat16) * 3.2)(D)), 'w_gate': _w((lambda *s: torch.randn(*s, dtype=torch.bfloat16) * 0.1)(D, F)), 'w_up': _w((lambda *s: torch.randn(*s, dtype=torch.bfloat16) * 0.1)(D, F)), 'w_down': _w((lambda *s: torch.randn(*s, dtype=torch.bfloat16) * 0.1)(F, D))}
    _B_in = _B_setup()
    return {'A_x': _A_in['x'], 'A_wqkv': _A_in['wqkv'], 'A_wo': _A_in['wo'], 'B_x': _B_in['x'], 'B_w_r': _B_in['w_r'], 'B_w_gate': _B_in['w_gate'], 'B_w_up': _B_in['w_up'], 'B_w_down': _B_in['w_down'], 'c': _w((lambda *s: torch.randn(*s, dtype=torch.bfloat16) * 0.1)(1, 640) * 8.0), 'w_mod': _w((lambda *s: torch.randn(*s, dtype=torch.bfloat16) * 0.1)(640, 6 * 640) * 640 ** (-0.5) * 8.0)}

def reference(A_x, A_wqkv, A_wo, B_x, B_w_r, B_w_gate, B_w_up, B_w_down, c, w_mod):

    def _A_ref(x, wqkv, wo):
        B, S, D = x.shape
        H = 32
        Dh = D // H
        W, dil = (8, 2)
        qkv = (lambda x, *d: x.permute(*d))((x @ wqkv).reshape(B, S, 3, H, Dh), 2, 0, 3, 1, 4)
        q, k, v = (qkv[0], qkv[1], qkv[2])
        scale = Dh ** (-0.5)
        pos = torch.arange(S)
        off = torch.arange(W) * dil
        idx = pos[:, None] - off[None, :]
        mask = idx >= 0
        idx_c = torch.where(mask, idx, 0).reshape(-1)
        kg = k[:, :, idx_c, :].reshape(B, H, S, W, Dh)
        vg = v[:, :, idx_c, :].reshape(B, H, S, W, Dh)
        logits = torch.einsum('bhsd,bhswd->bhsw', q, kg) * scale
        logits = torch.where(mask[None, None, :, :], logits, -1000000000.0)
        attn = _softmax(logits, axis=-1)
        o = torch.einsum('bhsw,bhswd->bhsd', attn, vg)
        return (lambda x, *d: x.permute(*d))(o, 0, 2, 1, 3).reshape(B, S, D) @ wo

    def _B_ref(x, w_r, w_gate, w_up, w_down):
        B, S, D = x.shape
        C = 1
        r = x @ w_r
        idx = torch.argsort(-r, axis=-1)[:, :C]
        idx_e = (lambda x, n, axis: torch.repeat_interleave(x, n, dim=axis))(idx.reshape(B, C, 1), D, axis=2)
        x_sel = (lambda x, i, axis: torch.take_along_dim(x, i, dim=axis))(x, idx_e, axis=1)
        g = _silu(x_sel @ w_gate)
        u = x_sel @ w_up
        y = g * u @ w_down
        r_sel = _sigmoid((lambda x, i, axis: torch.take_along_dim(x, i, dim=axis))(r, idx, axis=1))
        y = y * r_sel.reshape(B, C, 1)
        b_off = (torch.arange(B) * S).reshape(B, 1)
        flat_idx = (idx + b_off).reshape(B * C)
        zero = (x * 0.0).reshape(B * S, D)
        upd = _scatter_add(zero, flat_idx, y.reshape(B * C, D), axis=0)
        return x + upd.reshape(B, S, D)
    x = A_x
    mod = (_silu(c) @ w_mod).reshape(c.shape[0], 6, 1, -1)
    sa, ca, ga, sb, cb, gb = (mod[:, 0].clone(), mod[:, 1].clone(), mod[:, 2].clone(), mod[:, 3].clone(), mod[:, 4].clone(), mod[:, 5].clone())
    h = _layernorm(x, axis=-1) * (1 + ca) + sa
    x = x + ga * _A_ref(h, A_wqkv, A_wo)
    h = _layernorm(x, axis=-1) * (1 + cb) + sb
    x = x + gb * _B_ref(h, B_w_r, B_w_gate, B_w_up, B_w_down)
    return x
```

```cpp
#include <cuda_runtime.h>
#include <cuda.h>
#include <cuda_bf16.h>
#include <stdint.h>

namespace {

constexpr int STAGE_A = 16384, STAGE_B0 = 24576, STAGE_B1 = 6144, STAGE = STAGE_A + STAGE_B0 + STAGE_B1;
constexpr int WO = 15360;
constexpr int OFF_FFN = 4 * WO, OFF_LM = 2 * STAGE, OFF_X2 = 12 * WO, OFF_OUT = OFF_X2 + 20480;
constexpr int OFF_H = 4 * STAGE, OFF_L = OFF_H + 9 * 2560, OFF_XS = OFF_H, OFF_RED = OFF_L;
constexpr int OFF_C1 = OFF_OUT + 20480, OFF_ACT = OFF_C1, OFF_PRM = OFF_C1 + 2560, OFF_SILU = OFF_PRM + 1600;
constexpr int OFF_KEY = OFF_SILU + 320, OFF_BAR = OFF_KEY + 128, OFF_TIME = OFF_BAR + 256, SMEM_BYTES = OFF_TIME + 1536;
static_assert(SMEM_BYTES <= 232448, "smem");
enum { R_GA = 0, R_SB = 160, R_C1 = 320, R_GB = 480, R_FIN = 640, R_P = 800 + R_C1, R_ONE = 704 };

enum { B_FULL = 0, B_EMPTY = 4, B_HALO = 8, B_TAB = 9, B_GO = 10, B_XS = 11, B_ACT = B_FULL, B_FFN = B_FULL + 1, B_WO0 = B_FULL + 2, B_WO1 = B_FULL + 3 };
enum { NB_PV = 1, NB_TURN = 2, NB_KEY = 4, NB_OUT = 5, NB_HELP = 6, NB_HALO = 7, NB_PUB = 8, NB_GO = 9 };

enum { M_EARLY = 0, M_ST1 = 32, M_EPOCH = 40, M_HALO = 48, M_ST2 = 208, M_CAND = 336, M_LATE = 368, M_YP = 400, M_O = 560, BOX = 1840 };
__device__ uint4 g_scratch[128 * BOX];

constexpr int N_FFN = 108;
#define XS_AT 1200
#define S0_AT 0
#define WPF_AT 4500
#define LATE_GAP 1500
#define PUB 3
#define NOPEN 768
#define NSET 3
#define TOUCH 1
#define FFN_EARLY 0
#define DRY 1
#define OUT_AT 600
#define WF_EARLY 1
#define XS_POS 0
#define NO_TPF 0
#define B0 2
#define WO_HOLD 8
#define POLL_AT 3400
#define S_GAP 1200
#define EARLY 2
#define OUT_GAP 200
#define BY_SM 1
#define FGO_STEP 3
constexpr int SPIN_LIMIT = 1 << 16;

struct Params {
  const __nv_bfloat16 *wmod, *c, *x;
  uint4* sc;
  uint32_t zero;
  const __nv_bfloat16 *wqkv, *wr, *wo, *wgate, *wup, *wdown;
  __nv_bfloat16* out;
  CUtensorMap xa, w0, w1, wm, woa, wob, wg, wu, wd, tg, tu, td, om;
};

__device__ __forceinline__ uint32_t clock32() {
  uint32_t c;
  asm volatile("mov.u32 %0, %%clock;" : "=r"(c));
  return c;
}
#define TSTAMP(i) do { } while (0)
#define TDUMP() do { } while (0)
#define TALIGN(k) do { } while (0)

__device__ __forceinline__ void mbar_init(uint32_t b, uint32_t c) { asm volatile("mbarrier.init.shared::cta.b64 [%0], %1;" ::"r"(b), "r"(c) : "memory"); }
__device__ __forceinline__ void mbar_expect_tx(uint32_t b, uint32_t n) { asm volatile("mbarrier.arrive.expect_tx.shared::cta.b64 _, [%0], %1;" ::"r"(b), "r"(n) : "memory"); }
__device__ __forceinline__ void mbar_arrive(uint32_t b) { asm volatile("mbarrier.arrive.shared::cta.b64 _, [%0];" ::"r"(b) : "memory"); }
__device__ __forceinline__ uint32_t map_to_cta(uint32_t a, uint32_t rank) {
  uint32_t r;
  asm("mapa.shared::cluster.u32 %0, %1, %2;" : "=r"(r) : "r"(a), "r"(rank));
  return r;
}
__device__ __forceinline__ void mbar_arrive_cluster(uint32_t b) { asm volatile("mbarrier.arrive.shared::cluster.b64 _, [%0];" ::"r"(b) : "memory"); }
__device__ __forceinline__ void mbar_wait(uint32_t b, uint32_t ph) {
  asm volatile("{.reg .pred p;\n"
               "RETRY: mbarrier.try_wait.parity.shared::cta.b64 p, [%0], %1;\n"
               "@!p bra RETRY;}" ::"r"(b), "r"(ph) : "memory");
}
__device__ __forceinline__ bool elect_one() {
  uint32_t r;
  asm volatile("{.reg .pred p; elect.sync _|p, 0xFFFFFFFF; selp.u32 %0, 1, 0, p;}" : "=r"(r));
  return r;
}
template <int ID, int N> __device__ __forceinline__ void bar_sync() { asm volatile("bar.sync %0, %1;" ::"n"(ID), "n"(N) : "memory"); }
template <int ID, int N> __device__ __forceinline__ void bar_arrive() { asm volatile("bar.arrive %0, %1;" ::"n"(ID), "n"(N) : "memory"); }
__device__ __forceinline__ void turn_wait(uint32_t id) { asm volatile("bar.sync %0, 256;" ::"r"(id) : "memory"); }
__device__ __forceinline__ void turn_pass(uint32_t id) { asm volatile("bar.arrive %0, 256;" ::"r"(id ^ 1) : "memory"); }
__device__ __forceinline__ void tma2(uint32_t dst, const CUtensorMap* m, uint32_t bar, int c0, int c1) {
  asm volatile("cp.async.bulk.tensor.2d.shared::cluster.global.mbarrier::complete_tx::bytes [%0], [%1, {%3, %4}], [%2];" ::"r"(dst), "l"(m), "r"(bar), "r"(c0), "r"(c1) : "memory");
}
__device__ __forceinline__ void tma3(uint32_t dst, const CUtensorMap* m, uint32_t bar, int c0, int c1, int c2) {
  asm volatile("cp.async.bulk.tensor.3d.shared::cluster.global.mbarrier::complete_tx::bytes [%0], [%1, {%3, %4, %5}], [%2];" ::"r"(dst), "l"(m), "r"(bar), "r"(c0), "r"(c1), "r"(c2) : "memory");
}
__device__ __forceinline__ void tma2_both(uint32_t dst, const CUtensorMap* m, uint32_t bar, int c0, int c1) {
  asm volatile("cp.async.bulk.tensor.2d.shared::cluster.global.mbarrier::complete_tx::bytes.multicast::cluster [%0], [%1, {%3, %4}], [%2], %5;"
               ::"r"(dst), "l"(m), "r"(bar), "r"(c0), "r"(c1), "h"((uint16_t)3) : "memory");
}
__device__ __forceinline__ void tma3_both(uint32_t dst, const CUtensorMap* m, uint32_t bar, int c0, int c1, int c2) {
  asm volatile("cp.async.bulk.tensor.3d.shared::cluster.global.mbarrier::complete_tx::bytes.multicast::cluster [%0], [%1, {%3, %4, %5}], [%2], %6;"
               ::"r"(dst), "l"(m), "r"(bar), "r"(c0), "r"(c1), "r"(c2), "h"((uint16_t)3) : "memory");
}
__device__ __forceinline__ void bulk_prefetch(const void* src, uint32_t bytes) {
  asm volatile("cp.async.bulk.prefetch.L2.global [%0], %1;" ::"l"(src), "r"(bytes) : "memory");
}
__device__ __forceinline__ void bulk_load(uint32_t dst, const void* src, uint32_t bytes, uint32_t bar) {
  asm volatile("cp.async.bulk.shared::cluster.global.mbarrier::complete_tx::bytes [%0], [%1], %2, [%3];" ::"r"(dst), "l"(src), "r"(bytes), "r"(bar) : "memory");
}
__device__ __forceinline__ void wg_fence() { asm volatile("wgmma.fence.sync.aligned;" ::: "memory"); }
__device__ __forceinline__ void wg_commit() { asm volatile("wgmma.commit_group.sync.aligned;" ::: "memory"); }
__device__ __forceinline__ void wg_wait() { asm volatile("wgmma.wait_group.sync.aligned 0;" ::: "memory"); }
__device__ __forceinline__ uint64_t make_desc(uint32_t addr, uint32_t lbo, uint32_t sbo, uint32_t mode) {
  return (uint64_t)((addr & 0x3FFFF) >> 4) | ((uint64_t)(lbo >> 4) << 16) | ((uint64_t)(sbo >> 4) << 32) | ((uint64_t)mode << 62);
}
__device__ __forceinline__ void ldsm4(uint32_t& r0, uint32_t& r1, uint32_t& r2, uint32_t& r3, uint32_t a) {
  asm volatile("ldmatrix.sync.aligned.m8n8.x4.shared.b16 {%0, %1, %2, %3}, [%4];" : "=r"(r0), "=r"(r1), "=r"(r2), "=r"(r3) : "r"(a) : "memory");
}
__device__ __forceinline__ void ldsm4(uint32_t* r, uint32_t a) { ldsm4(r[0], r[1], r[2], r[3], a); }
__device__ __forceinline__ void ldsm2(uint32_t* r, uint32_t a) {
  asm volatile("ldmatrix.sync.aligned.m8n8.x2.shared.b16 {%0, %1}, [%2];" : "=r"(r[0]), "=r"(r[1]) : "r"(a) : "memory");
}
__device__ __forceinline__ void ldsm4t(uint32_t* r, uint32_t a) {
  asm volatile("ldmatrix.sync.aligned.m8n8.x4.trans.shared.b16 {%0, %1, %2, %3}, [%4];" : "=r"(r[0]), "=r"(r[1]), "=r"(r[2]), "=r"(r[3]) : "r"(a) : "memory");
}
__device__ __forceinline__ void ldsm2t(uint32_t* r, uint32_t a) {
  asm volatile("ldmatrix.sync.aligned.m8n8.x2.trans.shared.b16 {%0, %1}, [%2];" : "=r"(r[0]), "=r"(r[1]) : "r"(a) : "memory");
}
__device__ __forceinline__ void ld_row(uint32_t (&r)[10], uint32_t a) {
  ldsm4(r, a);
  ldsm4(r + 4, a + 64);
  ldsm2(r + 8, a + 128);
}
__device__ __forceinline__ void stsm4(uint32_t a, const uint32_t* r) {
  asm volatile("stmatrix.sync.aligned.m8n8.x4.shared.b16 [%0], {%1, %2, %3, %4};" ::"r"(a), "r"(r[0]), "r"(r[1]), "r"(r[2]), "r"(r[3]) : "memory");
}
__device__ __forceinline__ void stsm2(uint32_t a, const uint32_t* r) {
  asm volatile("stmatrix.sync.aligned.m8n8.x2.shared.b16 [%0], {%1, %2};" ::"r"(a), "r"(r[0]), "r"(r[1]) : "memory");
}
__device__ __forceinline__ void lds4(uint32_t* r, uint32_t a) {
  asm volatile("ld.shared.v4.u32 {%0, %1, %2, %3}, [%4];" : "=r"(r[0]), "=r"(r[1]), "=r"(r[2]), "=r"(r[3]) : "r"(a) : "memory");
}
__device__ __forceinline__ uint32_t lds1(uint32_t a) {
  uint32_t v;
  asm volatile("ld.shared.u32 %0, [%1];" : "=r"(v) : "r"(a) : "memory");
  return v;
}
__device__ __forceinline__ void sts1(uint32_t a, uint32_t v) { asm volatile("st.shared.u32 [%0], %1;" ::"r"(a), "r"(v) : "memory"); }
__device__ __forceinline__ void sts2(uint32_t a, uint32_t v0, uint32_t v1) { asm volatile("st.shared.v2.u32 [%0], {%1, %2};" ::"r"(a), "r"(v0), "r"(v1) : "memory"); }
__device__ __forceinline__ void mma16(float (&d)[4], uint32_t a0, uint32_t a1, uint32_t a2, uint32_t a3, uint32_t b0, uint32_t b1, const float* c) {
  asm volatile("mma.sync.aligned.m16n8k16.row.col.f32.bf16.bf16.f32 {%0, %1, %2, %3}, {%4, %5, %6, %7}, {%8, %9}, {%10, %11, %12, %13};"
               : "=f"(d[0]), "=f"(d[1]), "=f"(d[2]), "=f"(d[3])
               : "r"(a0), "r"(a1), "r"(a2), "r"(a3), "r"(b0), "r"(b1), "f"(c[0]), "f"(c[1]), "f"(c[2]), "f"(c[3]));
}
__device__ __forceinline__ void mma16(float (&d)[4], const uint32_t* a, uint32_t b0, uint32_t b1, const float* c) { mma16(d, a[0], a[1], a[2], a[3], b0, b1, c); }
__device__ __forceinline__ void mma8(float (&d)[4], uint32_t a0, uint32_t a1, uint32_t b0, const float* c) {
  asm volatile("mma.sync.aligned.m16n8k8.row.col.f32.bf16.bf16.f32 {%0, %1, %2, %3}, {%4, %5}, {%6}, {%7, %8, %9, %10};"
               : "=f"(d[0]), "=f"(d[1]), "=f"(d[2]), "=f"(d[3]) : "r"(a0), "r"(a1), "r"(b0), "f"(c[0]), "f"(c[1]), "f"(c[2]), "f"(c[3]));
}
__device__ __forceinline__ uint32_t pack2(float lo, float hi) {
  uint32_t r;
  asm volatile("cvt.rn.bf16x2.f32 %0, %1, %2;" : "=r"(r) : "f"(hi), "f"(lo));
  return r;
}
__device__ __forceinline__ float bf_lo(uint32_t w) { return __uint_as_float(w << 16); }
__device__ __forceinline__ float bf_hi(uint32_t w) { return __uint_as_float(w & 0xFFFF0000u); }
__device__ __forceinline__ float bf_round(float v) { return __uint_as_float(pack2(0.f, v)); }
__device__ __forceinline__ uint32_t fma2(uint32_t a, uint32_t b, uint32_t c) {
  uint32_t r;
  asm("fma.rn.bf16x2 %0, %1, %2, %3;" : "=r"(r) : "r"(a), "r"(b), "r"(c));
  return r;
}
__device__ __forceinline__ float ex2(float v) {
  float r;
  asm("ex2.approx.ftz.f32 %0, %1;" : "=f"(r) : "f"(v));
  return r;
}
__device__ __forceinline__ float rcp(float v) {
  float r;
  asm("rcp.approx.ftz.f32 %0, %1;" : "=f"(r) : "f"(v));
  return r;
}
__device__ __forceinline__ float rsq(float v) {
  float r;
  asm("rsqrt.approx.ftz.f32 %0, %1;" : "=f"(r) : "f"(v));
  return r;
}
__device__ __forceinline__ float sigmoid(float v) { return rcp(1.f + ex2(v * -1.4426950408889634f)); }
__device__ __forceinline__ float f32(uint32_t v) { return __uint_as_float(v); }
__device__ __forceinline__ uint32_t u32(float v) { return __float_as_uint(v); }
__device__ __forceinline__ void ld_rlx4(uint32_t* v, const void* p) {
  asm volatile("ld.relaxed.gpu.global.v4.u32 {%0, %1, %2, %3}, [%4];" : "=r"(v[0]), "=r"(v[1]), "=r"(v[2]), "=r"(v[3]) : "l"(p) : "memory");
}
__device__ __forceinline__ void ld_rlx2(uint32_t* v, const void* p) {
  asm volatile("ld.relaxed.gpu.global.v2.u32 {%0, %1}, [%2];" : "=r"(v[0]), "=r"(v[1]) : "l"(p) : "memory");
}
__device__ __forceinline__ uint32_t ld_rlx1(const void* p) {
  uint32_t v;
  asm volatile("ld.relaxed.gpu.global.u32 %0, [%1];" : "=r"(v) : "l"(p) : "memory");
  return v;
}
__device__ __forceinline__ void st_rlx4(void* p, uint32_t a, uint32_t b, uint32_t c, uint32_t d) {
  asm volatile("st.relaxed.gpu.global.v4.u32 [%0], {%1, %2, %3, %4};" ::"l"(p), "r"(a), "r"(b), "r"(c), "r"(d) : "memory");
}
__device__ __forceinline__ void st_rlx4(void* p, const uint32_t* v) { st_rlx4(p, v[0], v[1], v[2], v[3]); }
__device__ __forceinline__ void st_rlx2(void* p, uint32_t a, uint32_t b) { asm volatile("st.relaxed.gpu.global.v2.u32 [%0], {%1, %2};" ::"l"(p), "r"(a), "r"(b) : "memory"); }
__device__ __forceinline__ void st_rlx1(void* p, uint32_t v) { asm volatile("st.relaxed.gpu.global.u32 [%0], %1;" ::"l"(p), "r"(v) : "memory"); }
template <int LUT> __device__ __forceinline__ uint32_t lop3(uint32_t a, uint32_t b, uint32_t c) {
  uint32_t r;
  asm volatile("lop3.b32 %0, %1, %2, %3, %4;" : "=r"(r) : "r"(a), "r"(b), "r"(c), "n"(LUT));
  return r;
}
__device__ __forceinline__ uint32_t tag(uint32_t w, uint32_t ep) { return lop3<0xD8>(w, ep, 1u); }
__device__ __forceinline__ uint32_t neq2(uint32_t a, uint32_t b, uint32_t e) { return lop3<0x7E>(a, b, e); }
__device__ __forceinline__ uint32_t next_epoch(uint32_t e) {
  asm volatile("add.u32 %0, %0, 1;" : "+r"(e));
  return e;
}
__device__ __forceinline__ void sched_fence(uint32_t zero) {
  asm volatile("{.reg .pred p; setp.ne.u32 p, %0, 0;\nSPIN: pmevent 0; @p bra.uni SPIN;}" ::"r"(zero) : "memory");
}
__device__ __forceinline__ void wait_until(uint32_t t) {
  while ((int)(clock32() - t) < 0) { }
}
__device__ __forceinline__ float shx(float v, int o) { return __shfl_xor_sync(0xFFFFFFFFu, v, o); }
template <int SCALE, class T> __device__ __forceinline__ T* at(T* base, uint32_t i) {
  T* r;
  asm volatile("mad.wide.u32 %0, %1, %2, %3;" : "=l"(r) : "r"(i), "n"(SCALE), "l"(base));
  return r;
}
template <uint32_t MASK> __device__ __forceinline__ bool retry(uint32_t bad, int& budget) {
  uint32_t r;
  asm volatile("{.reg .pred p, q; .reg .b32 t; add.s32 %1, %1, -1; setp.gt.s32 q, %1, 0; and.b32 t, %2, %3; setp.ne.and.u32 p, t, 0, q;\n"
               "vote.sync.any.pred p, p, 0xFFFFFFFF; selp.u32 %0, 1, 0, p;}" : "=r"(r), "+r"(budget) : "r"(bad), "n"(MASK));
  return r;
}
template <int N, int W> __device__ __forceinline__ uint32_t stale(const uint32_t (*v)[4], uint32_t ep) {
  uint32_t bad = neq2(v[0][W], v[N > 1][W], ep);
#pragma unroll
  for (int i = 2; i < N; i += 2) bad |= neq2(v[i][W], v[i + 1 < N ? i + 1 : i][W], ep);
  return bad;
}
__device__ __forceinline__ void ld_rlx4_stale(uint32_t* v, const void* p, uint32_t w, uint32_t ep) {
  asm volatile("{.reg .b128 q; .reg .pred p; .reg .b32 t; lop3.b32 t, %5, %6, 1, 0x28; setp.ne.u32 p, t, 0; mov.b128 q, {%0, %1, %2, %3};\n"
               "@p ld.relaxed.gpu.global.b128 q, [%4]; mov.b128 {%0, %1, %2, %3}, q;}"
               : "+r"(v[0]), "+r"(v[1]), "+r"(v[2]), "+r"(v[3]) : "l"(p), "r"(w), "r"(ep) : "memory");
}
template <int N, int S0, int S1, int W> __device__ __forceinline__ void gather_lazy(uint32_t (*v)[4], const uint4* p, uint32_t ep, int& budget) {
#pragma unroll
  for (int i = 0; i < 4 * N; ++i) {
    if ((i & 3) == W) v[i >> 2][W] = ~ep;
    else asm volatile("" : "=r"(v[i >> 2][i & 3]));
  }
#pragma unroll 1
  do {
#pragma unroll
    for (int i = 0; i < N; ++i) ld_rlx4_stale(v[i], p + (i & 1) * S0 + (i >> 1) * S1, v[i][W], ep);
  } while (retry<1>(stale<N, W>(v, ep), budget));
}
template <int N, int STRIDE, int W> __device__ __forceinline__ void gather(uint32_t (*v)[4], const uint4* p, uint32_t ep, int& budget) {
#pragma unroll 1
  do {
#pragma unroll
    for (int i = 0; i < N; ++i) ld_rlx4(v[i], p + i * STRIDE);
  } while (retry<1>(stale<N, W>(v, ep), budget));
}
__device__ __forceinline__ void row_stats(float (&s)[4], float& qlo, float& qhi, const uint32_t (&x)[5][4], const uint32_t (&b)[10], int gq) {
  const float z[4] = {0.f, 0.f, 0.f, 0.f};
  float q[4][4];
#pragma unroll
  for (int i = 0; i < 5; ++i) {
    mma16(s, x[i], b[2 * i], b[2 * i + 1], i ? s : z);
#pragma unroll
    for (int e = 0; e < 4; ++e) mma8(q[e], x[i][e & 2], x[i][(e & 2) + 1], x[i][e], i ? q[e] : z);
  }
  const bool odd = gq & 1;
  qlo = (odd ? q[0][1] : q[0][0]) + (odd ? q[2][1] : q[2][0]);
  qhi = (odd ? q[1][3] : q[1][2]) + (odd ? q[3][3] : q[3][2]);
}
__device__ __forceinline__ uint32_t norm_word(float s, float q, float& mean, float& rstd) {
  mean = s * (1.f / 640.f);
  rstd = rsq(fmaxf(fmaf(q, 1.f / 640.f, -mean * mean), 0.f) + 1e-5f);
  return pack2(-mean * bf_round(rstd), rstd);
}
__device__ __forceinline__ uint32_t dup_lo(uint32_t w) { return __byte_perm(w, 0u, 0x1010); }
__device__ __forceinline__ uint32_t dup_hi(uint32_t w) { return __byte_perm(w, 0u, 0x3232); }

__device__ __forceinline__ void wgmma_n192(float (&d)[96], const uint32_t (&a)[4], uint64_t db, int add) {
  asm volatile("{.reg .pred p; setp.ne.b32 p, %101, 0; wgmma.mma_async.sync.aligned.m64n192k16.f32.bf16.bf16 "
    "{%0, %1, %2, %3, %4, %5, %6, %7, %8, %9, %10, %11, %12, %13, %14, %15, "
    "%16, %17, %18, %19, %20, %21, %22, %23, %24, %25, %26, %27, %28, %29, %30, %31, "
    "%32, %33, %34, %35, %36, %37, %38, %39, %40, %41, %42, %43, %44, %45, %46, %47, "
    "%48, %49, %50, %51, %52, %53, %54, %55, %56, %57, %58, %59, %60, %61, %62, %63, "
    "%64, %65, %66, %67, %68, %69, %70, %71, %72, %73, %74, %75, %76, %77, %78, %79, "
    "%80, %81, %82, %83, %84, %85, %86, %87, %88, %89, %90, %91, %92, %93, %94, %95}, "
    "{%96, %97, %98, %99}, %100, p, 1, 1, 1;}"
    : "+f"(d[0]), "+f"(d[1]), "+f"(d[2]), "+f"(d[3]), "+f"(d[4]), "+f"(d[5]), "+f"(d[6]), "+f"(d[7]),
      "+f"(d[8]), "+f"(d[9]), "+f"(d[10]), "+f"(d[11]), "+f"(d[12]), "+f"(d[13]), "+f"(d[14]), "+f"(d[15]),
      "+f"(d[16]), "+f"(d[17]), "+f"(d[18]), "+f"(d[19]), "+f"(d[20]), "+f"(d[21]), "+f"(d[22]), "+f"(d[23]),
      "+f"(d[24]), "+f"(d[25]), "+f"(d[26]), "+f"(d[27]), "+f"(d[28]), "+f"(d[29]), "+f"(d[30]), "+f"(d[31]),
      "+f"(d[32]), "+f"(d[33]), "+f"(d[34]), "+f"(d[35]), "+f"(d[36]), "+f"(d[37]), "+f"(d[38]), "+f"(d[39]),
      "+f"(d[40]), "+f"(d[41]), "+f"(d[42]), "+f"(d[43]), "+f"(d[44]), "+f"(d[45]), "+f"(d[46]), "+f"(d[47]),
      "+f"(d[48]), "+f"(d[49]), "+f"(d[50]), "+f"(d[51]), "+f"(d[52]), "+f"(d[53]), "+f"(d[54]), "+f"(d[55]),
      "+f"(d[56]), "+f"(d[57]), "+f"(d[58]), "+f"(d[59]), "+f"(d[60]), "+f"(d[61]), "+f"(d[62]), "+f"(d[63]),
      "+f"(d[64]), "+f"(d[65]), "+f"(d[66]), "+f"(d[67]), "+f"(d[68]), "+f"(d[69]), "+f"(d[70]), "+f"(d[71]),
      "+f"(d[72]), "+f"(d[73]), "+f"(d[74]), "+f"(d[75]), "+f"(d[76]), "+f"(d[77]), "+f"(d[78]), "+f"(d[79]),
      "+f"(d[80]), "+f"(d[81]), "+f"(d[82]), "+f"(d[83]), "+f"(d[84]), "+f"(d[85]), "+f"(d[86]), "+f"(d[87]),
      "+f"(d[88]), "+f"(d[89]), "+f"(d[90]), "+f"(d[91]), "+f"(d[92]), "+f"(d[93]), "+f"(d[94]), "+f"(d[95])
    : "r"(a[0]), "r"(a[1]), "r"(a[2]), "r"(a[3]), "l"(db), "r"(add));
}
__device__ __forceinline__ void wgmma_n48(float (&d)[24], const uint32_t (&a)[4], uint64_t db, int add) {
  asm volatile("{.reg .pred p; setp.ne.b32 p, %29, 0; wgmma.mma_async.sync.aligned.m64n48k16.f32.bf16.bf16 "
    "{%0, %1, %2, %3, %4, %5, %6, %7, %8, %9, %10, %11, %12, %13, %14, %15, "
    "%16, %17, %18, %19, %20, %21, %22, %23}, "
    "{%24, %25, %26, %27}, %28, p, 1, 1, 1;}"
    : "+f"(d[0]), "+f"(d[1]), "+f"(d[2]), "+f"(d[3]), "+f"(d[4]), "+f"(d[5]), "+f"(d[6]), "+f"(d[7]),
      "+f"(d[8]), "+f"(d[9]), "+f"(d[10]), "+f"(d[11]), "+f"(d[12]), "+f"(d[13]), "+f"(d[14]), "+f"(d[15]),
      "+f"(d[16]), "+f"(d[17]), "+f"(d[18]), "+f"(d[19]), "+f"(d[20]), "+f"(d[21]), "+f"(d[22]), "+f"(d[23])
    : "r"(a[0]), "r"(a[1]), "r"(a[2]), "r"(a[3]), "l"(db), "r"(add));
}
__device__ __forceinline__ void wgmma_n80(float (&d)[40], const uint32_t (&a)[4], uint64_t db, int add) {
  asm volatile("{.reg .pred p; setp.ne.b32 p, %45, 0; wgmma.mma_async.sync.aligned.m64n80k16.f32.bf16.bf16 "
    "{%0, %1, %2, %3, %4, %5, %6, %7, %8, %9, %10, %11, %12, %13, %14, %15, "
    "%16, %17, %18, %19, %20, %21, %22, %23, %24, %25, %26, %27, %28, %29, %30, %31, "
    "%32, %33, %34, %35, %36, %37, %38, %39}, "
    "{%40, %41, %42, %43}, %44, p, 1, 1, 1;}"
    : "+f"(d[0]), "+f"(d[1]), "+f"(d[2]), "+f"(d[3]), "+f"(d[4]), "+f"(d[5]), "+f"(d[6]), "+f"(d[7]),
      "+f"(d[8]), "+f"(d[9]), "+f"(d[10]), "+f"(d[11]), "+f"(d[12]), "+f"(d[13]), "+f"(d[14]), "+f"(d[15]),
      "+f"(d[16]), "+f"(d[17]), "+f"(d[18]), "+f"(d[19]), "+f"(d[20]), "+f"(d[21]), "+f"(d[22]), "+f"(d[23]),
      "+f"(d[24]), "+f"(d[25]), "+f"(d[26]), "+f"(d[27]), "+f"(d[28]), "+f"(d[29]), "+f"(d[30]), "+f"(d[31]),
      "+f"(d[32]), "+f"(d[33]), "+f"(d[34]), "+f"(d[35]), "+f"(d[36]), "+f"(d[37]), "+f"(d[38]), "+f"(d[39])
    : "r"(a[0]), "r"(a[1]), "r"(a[2]), "r"(a[3]), "l"(db), "r"(add));
}

__device__ __forceinline__ constexpr int wo_off(int i) { return (i < 4 ? 8 + i : i - 4) * WO; }
__device__ __forceinline__ void load_stage(const Params& P, uint32_t sb, int st, int j, int g, int rank) {
  const uint32_t fb = sb + OFF_BAR + 8 * (B_FULL + (st & 3)), a = sb + (st & 3) * STAGE;
  mbar_expect_tx(fb, STAGE);
  tma2(a, &P.xa, fb, 640 * rank + 64 * st, 128 * j);
  tma3_both(a + STAGE_A + rank * (STAGE_B0 / 2), &P.w0, fb, 80 * g, 64 * st + 32 * rank, 0);
  tma3_both(a + STAGE_A + STAGE_B0 + rank * (STAGE_B1 / 2), &P.w1, fb, 80 * g + 64, 64 * st + 32 * rank, 0);
}

__device__ __forceinline__ void run_producer(const Params& P, uint8_t* sm, uint32_t sb, int b) {
  const int rank = b & 1, g = (b >> 1) & 7, j = b >> 4;
  const uint32_t bar = sb + OFF_BAR;
  bar_sync<NB_GO, 160>();
#pragma unroll 1
  for (int st = EARLY; st < 10; ++st) {
    mbar_wait(bar + 8 * (B_EMPTY + (st & 3)), ((st >> 2) + 1) & 1);
    if (elect_one()) {
      load_stage(P, sb, st, j, g, rank);
      const int i = st - EARLY;
      if ((i & 1) && i < 6 && b < N_FFN) {
        asm volatile("mbarrier.expect_tx.shared::cta.b64 [%0], 2560;" ::"r"(bar + 8 * B_HALO) : "memory");
        tma3(sb + OFF_L, &P.tg + (i >> 1), bar + 8 * B_HALO, i < 5 ? 64 * (b >> 2) : 0, i < 5 ? 0 : 16 * b, i < 5 ? 2 * rank + (g & 1) : 0);
      }
      if (i < 5) bulk_prefetch(P.wmod + (5 * b + i) * 3840 + 1280, 5120);
      else if (i == 5) bulk_prefetch(P.wo + b * 3200, 6400);
    }
  }
  TSTAMP(1);
#pragma unroll 1
  for (int i = 0; i < 8; ++i) {
    if (i == WO_HOLD) bar_sync<NB_HALO, 96>();
    if (i < 2 || i == 4 || i == 7) mbar_wait(bar + 8 * (B_EMPTY + (i < 2 ? 2 + i : i & 1)), i < 2);
    if (elect_one()) {
      const uint32_t fb = bar + 8 * (i ? B_WO1 : B_WO0), a = sb + (i < 4 ? 8 + i : i - 4) * WO;
      if (i == 0) {
        mbar_expect_tx(bar + 8 * B_XS, 25600);
        tma2(sb + OFF_LM, &P.wm, bar + 8 * B_XS, 1280 + 80 * (b & 31), 160 * (b >> 5));
      }
      if (i < 2) mbar_expect_tx(fb, i ? 7 * 12800 : 12800);
      if ((i & 1) == rank) {
        const int k0 = 80 * (i ? i - (i <= g) : g);
        tma3_both(a, &P.woa, fb, 80 * g, k0, 0);
        tma2_both(a + 10240, &P.wob, fb, 80 * g + 64, k0);
      }
    }
  }
  if (WO_HOLD > 7) bar_sync<NB_HALO, 96>();
  TSTAMP(3);
  if (b < N_FFN) {
    if (elect_one()) {
      mbar_expect_tx(bar + 8 * B_ACT, 1024);
      mbar_expect_tx(bar + 8 * B_FFN, 61440);
    }
#pragma unroll 1
    for (int i = 0; i < 4; ++i) {
      if (i == FFN_EARLY) {
        mbar_wait(bar + 8 * B_TAB, 1);
        mbar_wait(bar + 8 * B_GO, 1);
      }
      if (elect_one()) tma3(sb + OFF_FFN + 10240 * i, &P.wg + (i >> 1), bar + 8 * B_FFN, 32 * (b >> 1), 0, 2 * rank + (i & 1));
    }
    if (elect_one()) tma3(sb + OFF_FFN + 40960, &P.wd, bar + 8 * B_FFN, 0, 16 * b, 0);
  }
  TSTAMP(4);
}

__device__ __forceinline__ void run_helper(const Params& P, uint8_t* sm, uint32_t sb, int b, int hw, uint32_t ep, int budget, uint32_t poll_at) {
  const int h = threadIdx.x - 256, lane = h & 31, gq = lane >> 2, t = lane & 3, rank = b & 1, g = (b >> 1) & 7, j = b >> 4;
  const uint32_t bar = sb + OFF_BAR, prm = sb + OFF_PRM;
  uint4* const box = P.sc + b * BOX;
  const bool main20 = lane < 20;
  const int fin = 128 * (b >> 4) + 16 * ((b >> 2) & 3) + 2 * (b & 3) + 64 * (lane & 1) + 4 * (lane & 2);
  const int which = main20 ? 2 - hw : 3, fsl = (fin * 205) >> 14;
  const int q4 = main20 ? lane : hw < 2 ? min(10 * hw + lane - 20, 19) : (fin - 80 * fsl) >> 2;
  uint32_t wr[2];
  asm volatile("ld.global.nc.v2.u32 {%0, %1}, [%2];" : "=r"(wr[0]), "=r"(wr[1]) : "l"(P.wr + 80 * g + 4 * q4));
  uint32_t cw;
  asm volatile("ld.global.nc.u32 %0, [%1];" : "=r"(cw) : "l"(P.c + 160 * (b >> 5) + 2 * min(h, 79)));
  sts1(sb + OFF_SILU + 4 * min(h, 79), pack2(bf_lo(cw) * sigmoid(bf_lo(cw)), bf_hi(cw) * sigmoid(bf_hi(cw))));
  if (h < 4) sts1(prm + R_ONE + 4 * h, 0x3F803F80u);
  wait_until(poll_at);
  {
    uint32_t v[4][4];
    const int h80 = min(h, 79);
    const uint4* src = at<16>(P.sc, (h80 >> 2) * BOX + 4 * j + (h80 & 3));
#pragma unroll 1
    do {
#pragma unroll
      for (int i = 0; i < 4; ++i) ld_rlx4(v[i], src + i * 20 * BOX);
    } while (retry<~0u>(stale<4, 2>(v, ep), budget));
#pragma unroll
    for (int i = 0; i < 4; ++i) sts2(sb + OFF_C1 + 16 * h80 + 1280 * (i & 1) + (i < 2 ? 8 : 0), v[i][0], v[i][1]);
    mbar_arrive(bar + 8 * B_TAB);
  }
  TSTAMP(3);
  bar_sync<NB_GO, 160>();
#pragma unroll 1
  for (int i = h; i < NOPEN; i += 96) st_rlx4(at<16>(box + M_HALO, i), ~ep, ~ep, ~ep, ~ep);
  bar_sync<NB_HELP, 96>();
  TSTAMP(5);

  {
    float d0[4] = {0.f, 0.f, 0.f, 0.f}, d1[4] = {0.f, 0.f, 0.f, 0.f};
    uint32_t wa = sb + OFF_LM + (8 * (lane >> 4) + (lane & 7)) * 160 + 64 * hw + (lane & 8) * 2, sa = sb + OFF_SILU + (lane >> 3) * 16;
    mbar_wait(bar + 8 * B_XS, 1);
    if (hw == 2) {
      uint32_t hv[5][4] = {};
      mbar_wait(bar + 8 * B_EMPTY, 0);
      if (j > 0) gather<5, 32, 0>(hv, at<16>(box + (M_HALO - 16 * BOX), lane), ep, budget);
#pragma unroll
      for (int q = 0; q < 5; ++q) stsm4(sb + OFF_H + 512 * q + 16 * lane, hv[q]);
      bar_arrive<NB_HALO, 96>();
      TSTAMP(4);
    }
    mbar_wait(bar + 8 * (B_EMPTY + 1), 0);
    TSTAMP(6);
#pragma unroll 1
    for (int u = 0; u < 5; ++u) {
      uint32_t a[4][4], s[4];
      ldsm4(s, sa);
#pragma unroll
      for (int i = 0; i < 4; ++i) ldsm4t(a[i], wa + (i >> 1) * 2560 + (i & 1) * 32);
      mma16(d0, a[0], s[0], s[1], d0);
      mma16(d1, a[1], s[0], s[1], d1);
      mma16(d0, a[2], s[2], s[3], d0);
      mma16(d1, a[3], s[2], s[3], d1);
      wa += 5120;
      sa += 64;
    }
    const float v = t & 2 ? (t & 1 ? d1[2] : d1[0]) : (t & 1 ? d0[2] : d0[0]);
    if (32 * hw + 8 * t < 80) st_rlx1(at<4>(box + M_LATE, 32 * hw + 8 * t + gq), tag(u32(v), ep));
  }
  TSTAMP(7);
  wait_until(clock32() + LATE_GAP);
  {
    uint32_t v[4][4];
    const uint4* src = at<16>(P.sc + M_LATE, (8 * which + (main20 || hw < 2 ? g : fsl & 7)) * BOX + q4);
#pragma unroll 1
    do {
#pragma unroll
      for (int i = 0; i < 4; ++i) ld_rlx4(v[i], src + i * 32 * BOX);
    } while (retry<1>(stale<4, 0>(v, ep) | stale<4, 1>(v, ep) | stale<4, 2>(v, ep) | stale<4, 3>(v, ep), budget));
    const uint32_t one = which == 2 ? 0x3F803F80u : 0u;
    uint32_t w[2], pw[2];
#pragma unroll
    for (int e = 0; e < 2; ++e) {
      w[e] = fma2(pack2(f32(v[0][2 * e]) + f32(v[1][2 * e]) + f32(v[2][2 * e]) + f32(v[3][2 * e]),
                        f32(v[0][2 * e + 1]) + f32(v[1][2 * e + 1]) + f32(v[2][2 * e + 1]) + f32(v[3][2 * e + 1])), 0x3F803F80u, one);
      pw[e] = fma2(w[e], wr[e], 0x80008000u);
    }
    const uint32_t dst = prm + (main20 || hw < 2 ? 160 * which + 8 * q4 : R_FIN + 8 * (lane & 3));
    sts2(dst, w[0], w[1]);
    sts2(dst + 800, pw[0], pw[1]);
    float s = main20 ? bf_lo(pw[0]) + bf_hi(pw[0]) + bf_lo(pw[1]) + bf_hi(pw[1]) : 0.f;
#pragma unroll
    for (int o = 16; o > 0; o >>= 1) s += shx(s, o);
    sts1(sb + OFF_KEY + 64 + 4 * hw, u32(s));
    mbar_arrive(bar + 8 * B_TAB);
    mbar_wait(bar + 8 * B_TAB, 1);
  }
  TSTAMP(8);

  uint32_t ckey = 0;
  uint4* const odst = reinterpret_cast<uint4*>(P.out + (256 * j + rank) * 640 + 80 * g);
  if (hw == 0) {
    const uint32_t tile = min(4 * (lane & 3) + (lane >> 3), 9) * 16;
    uint32_t c1[4], sv[4], gb[4], x[4];
    ldsm4(c1, prm + R_C1 + tile);
    ldsm4(sv, prm + R_SB + tile);
    ldsm4(gb, prm + (lane & 4 ? R_GB + tile : R_ONE));
    const uint32_t bc = lds1(sb + OFF_KEY + 68), keep = gq & 4 ? ~0u : 0u;
    uint4* const cdst = at<16>(box + M_CAND, lane);
    uint32_t crow;
#pragma unroll 1
    for (int pass = DRY; pass < 2; ++pass) {
      if (pass) bar_sync<NB_KEY, 288>();
      uint32_t k0, k1;
      asm volatile("ld.shared.v2.u32 {%0, %1}, [%2];" : "=r"(k0), "=r"(k1) : "r"(sb + OFF_KEY + 8 * (lane & 7)) : "memory");
      ckey = __reduce_max_sync(0xFFFFFFFFu, k0);
      crow = (~ckey >> 1) & 127;
      TSTAMP(9);
      ldsm4(x, sb + OFF_X2 + crow * 160 + tile);
      const uint32_t nw = __shfl_sync(0xFFFFFFFFu, k1, crow >> 4), rs = dup_hi(nw), nm = dup_lo(nw);
#pragma unroll
      for (int e = 0; e < 4; ++e) x[e] = fma2(gb[e], fma2(fma2(x[e], rs, nm), c1[e], sv[e]), x[e] & keep);
      st_rlx4(cdst, tag(x[0], ep + 1 - pass), x[1], gq == 2 ? ckey : x[2], gq == 2 ? bc : x[3]);
    }
    bar_arrive<NB_PUB, 352>();
    TSTAMP(10);
    bar_sync<NB_OUT, 288>();
    uint32_t next = clock32() + OUT_AT;
#pragma unroll 1
    for (int u = 0; u < 8; ++u) {
      wait_until(next);
      next += OUT_GAP;
      if (u != crow >> 4 && elect_one())
        asm volatile("cp.async.bulk.tensor.2d.global.shared::cta.bulk_group [%0, {%2, %3}], [%1];"
                     ::"l"(&P.om), "r"(sb + OFF_OUT + 2560 * u), "r"(640 * rank + 80 * g), "r"(128 * j + 16 * u) : "memory");
    }
    asm volatile("cp.async.bulk.commit_group;" ::: "memory");
    TSTAMP(11);
  } else {
    bar_sync<NB_PUB, 352>();
    if (b >= 80) return;
  }
  uint32_t m[4][4] = {};
  gather<1, 0, 0>(m, at<16 * BOX>(P.sc + M_CAND + 8, 8 * (lane & 14) + (lane & 1)), ep, budget);
  const uint32_t wkey = __reduce_max_sync(0xFFFFFFFFu, m[0][2]), wtok = ~wkey & 2047;
  TSTAMP(12);
  if (hw == 0) {
    const uint32_t u = (~ckey >> 5) & 7, skip = ckey == wkey ? (~ckey >> 1) & 15 : 16;
#pragma unroll
    for (int i = 0; i < 5; ++i) {
      const uint32_t v = lane + 32 * i, r = (v * 205) >> 11;
      if (r != skip) *at<16>(odst, 2560 * u + v + 150 * r) = *reinterpret_cast<const uint4*>(sm + OFF_OUT + 2560 * u + 16 * v);
    }
    st_rlx1(at<4>(box + M_EPOCH, lane), ep);
    asm volatile("cp.async.bulk.wait_group.read 0;" ::: "memory");
    TSTAMP(15);
    TALIGN(1);
    return;
  } else {
    const int n = fin + hw - 1, cn = n - 80 * fsl;
    gather<1, 0, 0>(m, at<16>(P.sc + M_CAND, (16 * (wtok >> 8) + (wtok & 1) + 2 * (lane & 8 ? lane & 7 : fsl)) * BOX + (lane & 8 ? 8 : 16 + 4 * (cn >> 5) + ((cn >> 1) & 3))),
                    ep, budget);
    const uint32_t bw = cn & 16 ? (cn & 8 ? m[0][3] : m[0][2]) : (cn & 8 ? m[0][1] : m[0][0]);
    const uint32_t gw = lds1(prm + R_FIN + 8 * (lane & 3) + 4 * (b & 1));
    float r = f32(m[0][3]);
#pragma unroll
    for (int o = 1; o < 8; o <<= 1) r += shx(r, o);
    r = __shfl_sync(0xFFFFFFFFu, r, 8) + f32(wkey >> 31 ? wkey & 0x7FFFF800u : ~wkey | 0x7FFu);
    const float sg = bf_round(sigmoid(bf_round(r))), gv = bf_hi(gw << (32 - 16 * hw)), bv = bf_hi(bw << (32 - 16 * hw));
    __nv_bfloat16* const dst = at<2>(P.out, wtok * 640 + n);
    TSTAMP(13);
    const uint4* const src = at<16 * BOX>(P.sc + M_YP + 2 * b + hw - 1, min(lane, 26));
#pragma unroll 1
    for (int pass = DRY; pass < 2; ++pass) {
      if (pass) gather_lazy<4, 27 * BOX, 54 * BOX, 0>(m, src, ep, budget);
      TSTAMP(14);
      float y[4];
#pragma unroll
      for (int e = 0; e < 4; ++e) y[e] = lane < 27 ? (f32(m[0][e]) + f32(m[1][e])) + (f32(m[2][e]) + f32(m[3][e])) : 0.f;
      const bool u1 = lane & 1, u2 = lane & 2;
      const float e0 = (u1 ? y[1] : y[0]) + shx(u1 ? y[0] : y[1], 1), e1 = (u1 ? y[3] : y[2]) + shx(u1 ? y[2] : y[3], 1);
      float e = (u2 ? e1 : e0) + shx(u2 ? e0 : e1, 2);
#pragma unroll
      for (int o = 4; o < 32; o <<= 1) e += shx(e, o);
      if (lane < 4 * pass) *dst = __float2bfloat16(fmaf(gv, bf_round(bf_round(e) * sg), bv));
    }
  }
  TSTAMP(15);
}

#define ACC(part, i, e) ((i) < 8 ? accA[32 * (part) + 4 * ((i) & 7) + (e)] : accB[8 * (part) + 4 * ((i) & 1) + (e)])
__device__ __forceinline__ constexpr int kpos(int i) { return i == 2 ? 8 : i == 7 ? 9 : i - (i > 2) - (i > 7); }

__device__ __forceinline__ void run_consumer(const Params& P, uint8_t* sm, uint32_t sb, int b, int warp, uint32_t ep, int budget) {
  const int tid = threadIdx.x, lane = tid & 31, gq = lane >> 2, t = lane & 3, p = warp >> 2, wq = warp & 3, rb = warp ^ 4;
  const int rank = b & 1, g = (b >> 1) & 7, j = b >> 4;
  const uint32_t bar = sb + OFF_BAR;
  uint4* const box = P.sc + b * BOX;
  const float z4[4] = {0.f, 0.f, 0.f, 0.f};

  uint32_t nrm[4];
  {
    uint32_t x[5][4], ones[10];
#pragma unroll
    for (int i = 0; i < 10; ++i) ones[i] = 0x3F803F80u;
    uint4* const dst = at<8>(box + M_ST1, tid >> 4);
    const uint4* const src = at<8>(P.sc + M_ST1, (16 * j + 2 * rb) * 2 * BOX + 2 * gq + rank);
    mbar_wait(bar + 8 * B_XS, 0);
    TSTAMP(4);
#pragma unroll
    for (int i = 0; i < 5; ++i) lds4(x[i], sb + OFF_XS + (tid >> 4) * 1280 + (lane & 15) * 16 + 256 * i);
    float s[4], qlo, qhi, mean, rstd;
    row_stats(s, qlo, qhi, x, ones, gq);
    const float q = __shfl_sync(0xFFFFFFFFu, qlo + qhi, 4 * gq + (gq >> 1));
    float v = t & 1 ? q : s[0] + s[2];
    v += shx(v, 4);
    v += shx(v, 8);
    const uint32_t nw = norm_word(v, shx(v, 1), mean, rstd);
    if ((lane & 15) == 0) st_rlx2(dst, nw, ep);
    TSTAMP(5);
    asm volatile("setmaxnreg.inc.sync.aligned.u32 224;");
    uint32_t n0[2], n1[2];
#pragma unroll 1
    do {
      ld_rlx2(n0, src);
      ld_rlx2(n1, src + BOX);
    } while (retry<~0u>(neq2(n0[1], n1[1], ep), budget));
    nrm[0] = dup_hi(n0[0]); nrm[1] = dup_hi(n1[0]); nrm[2] = dup_lo(n0[0]); nrm[3] = dup_lo(n1[0]);
  }
  TSTAMP(6);
  mbar_wait(bar + 8 * B_TAB, 0);
  if (warp == 0) bar_arrive<NB_GO, 160>();

  float accA[96], accB[24];
#pragma unroll
  for (int i = 0; i < 96; ++i) asm volatile("" : "=f"(accA[i]));
#pragma unroll
  for (int i = 0; i < 24; ++i) asm volatile("" : "=f"(accB[i]));
  uint32_t xr[5][4];
#pragma unroll
  for (int i = 0; i < 20; ++i) asm volatile("" : "=r"(xr[i >> 2][i & 3]));
  const uint32_t turn = NB_TURN + p;
  uint4* opub;
  {
    uint32_t la = sb + (16 * rb + (lane & 15)) * 128 + (((lane >> 4) ^ (lane & 7)) << 4);
    uint32_t rel = map_to_cta(bar + 8 * B_EMPTY, lane & 1), c1a = sb + OFF_C1 + 16 * t;
    uint64_t d0 = make_desc(sb + STAGE_A, 4096, 1024, 1);
    int kx = 5 * g, lim = 0;
    uint32_t cw[4][4];
#pragma unroll
    for (int k = 0; k < 4; ++k) lds4(cw[k], c1a + 64 * k);
    if (p == 1) turn_pass(turn);
#pragma unroll 1
    for (int st = 0; st < 10; ++st) {
      uint32_t raw[4][4], af[4][4];
      mbar_wait(bar + 8 * (B_FULL + (st & 3)), (st >> 2) & 1);
#pragma unroll
      for (int k = 0; k < 4; ++k) ldsm4(raw[k], la ^ (32 * k));
      if ((uint32_t)(kx + 4) < 8u) {
#pragma unroll
        for (int i = 0; i < 5; ++i)
          if ((uint32_t)(kx + i) < 4u) ldsm4(xr[i], la ^ (32 * (kx + i)));
      }
#pragma unroll
      for (int k = 0; k < 16; ++k) raw[k >> 2][k & 3] = fma2(raw[k >> 2][k & 3], nrm[k & 1], nrm[2 + (k & 1)]);
      wg_wait();
      if (lane < lim) mbar_arrive_cluster(rel + 8 * ((st - 1) & 3));
#pragma unroll
      for (int k = 0; k < 16; ++k) af[k >> 2][k & 3] = fma2(raw[k >> 2][k & 3], cw[k >> 2][(k >> 1) & 1], cw[k >> 2][2 + ((k >> 1) & 1)]);
#pragma unroll
      for (int k = 0; k < 4; ++k) lds4(cw[k], c1a + 256 + 64 * k);
      wg_fence();
      turn_wait(turn);
      if (st == 0) TSTAMP(7);
      constexpr uint64_t D1 = (STAGE_B0 >> 4) + ((uint64_t)64 << 16) - ((uint64_t)256 << 16) + ((uint64_t)16 << 32) - ((uint64_t)64 << 32) + ((uint64_t)2 << 62);
#pragma unroll
      for (int k = 0; k < 4; ++k) {
        wgmma_n192(accA, af[k], d0 + ((k >> 1) * (STAGE_B0 / 2) + (k & 1) * 2048 >> 4), k ? 1 : st);
        wgmma_n48(accB, af[k], d0 + (D1 + ((k >> 1) * (STAGE_B1 / 2) + (k & 1) * 512 >> 4)), k ? 1 : st);
      }
      wg_commit();
      turn_pass(turn);
      const int step = (st & 3) == 3 ? -3 * STAGE : STAGE;
      la += step;
      d0 += step >> 4;
      c1a += 256;
      kx -= 4;
      lim = 2;
    }
    opub = at<16>(box + M_O, tid);
    sched_fence(P.zero);
    wg_wait();
    if (lane < 2) mbar_arrive_cluster(rel + 8);
  }
  TSTAMP(8);

  uint32_t o[5][4];

  {
    uint32_t hi[20], vl[10], kl[10], kh[10], vv[20], qf[4][4], qs[4][2];
    const uint32_t ha = sb + OFF_H + rb * 2560 + 16 * lane, lo = sb + OFF_L + rb * 1280 + 16 * lane;
#pragma unroll
    for (int i = 0; i < 10; ++i) {
      hi[kpos(i)] = pack2(ACC(1, i, 2), ACC(1, i, 3));
      hi[10 + i] = pack2(ACC(2, i, 2), ACC(2, i, 3));
    }
#pragma unroll
    for (int q = 0; q < 5; ++q) hi[4 * q] = tag(hi[4 * q], ep);
    if (rb == 7) {
#pragma unroll
      for (int q = 0; q < 5; ++q) st_rlx4(opub + (M_HALO - M_O - 96 + 32 * q), hi + 4 * q);
    }
    sched_fence(P.zero);
#pragma unroll
    for (int q = 0; q < 5; ++q) stsm4(ha + 2560 + 512 * q, hi + 4 * q);
#pragma unroll
    for (int i = 0; i < 10; ++i) vl[i] = pack2(ACC(2, i, 0), ACC(2, i, 1));
    stsm4(lo, vl);
    stsm4(lo + 512, vl + 4);
    stsm2(lo + 1024, vl + 8);
    __syncwarp();
    if (lane == 0) mbar_arrive(bar + 8 * B_HALO);
#pragma unroll
    for (int i = 0; i < 10; ++i) kl[kpos(i)] = pack2(ACC(1, i, 0), ACC(1, i, 1));
#pragma unroll
    for (int hd = 0; hd < 4; ++hd) {
      const int f0 = 5 * (hd >> 1) + 3 * (hd & 1), sg = 5 * (hd >> 1) + 2;
      const bool mine = (t >> 1) == (hd & 1);
#pragma unroll
      for (int e = 0; e < 4; ++e) qf[hd][e] = pack2(ACC(0, f0 + (e >> 1), 2 * (e & 1)), ACC(0, f0 + (e >> 1), 2 * (e & 1) + 1));
#pragma unroll
      for (int e = 0; e < 2; ++e) {
        if (!(hd & 1)) qs[hd + 1][e] = pack2(ACC(0, sg, 2 * e), ACC(0, sg, 2 * e + 1));
        qs[hd][e] = mine ? qs[hd | 1][e] : 0u;
      }
    }
    float S0[4][4], S1[4][4], S2[4][4];
    ldsm4t(vl, lo);
    ldsm4t(vl + 4, lo + 512);
    ldsm2t(vl + 8, lo + 1024);
    sched_fence(P.zero);
#pragma unroll
    for (int hd = 0; hd < 4; ++hd) {
      mma16(S1[hd], qf[hd], kl[2 * hd], kl[2 * hd + 1], z4);
      mma16(S2[hd], qf[hd], hi[2 * hd], hi[2 * hd + 1], z4);
    }
#pragma unroll
    for (int hd = 0; hd < 4; ++hd) {
      mma8(S1[hd], qs[hd][0], qs[hd][1], kl[8 + (hd >> 1)], S1[hd]);
      mma8(S2[hd], qs[hd][0], qs[hd][1], hi[8 + (hd >> 1)], S2[hd]);
    }
    TSTAMP(9);
    mbar_wait(bar + 8 * B_HALO, 0);
    if (rb == 0) bar_sync<NB_HALO, 96>();
    TSTAMP(10);
    ldsm4(kh, ha);
    ldsm4(kh + 4, ha + 512);
    ldsm2(kh + 8, ha + 1024);
#pragma unroll
    for (int i = 0; i < 5; ++i) ldsm4t(vv + 4 * i, sb + OFF_H + 1280 + (rb + ((lane >> 3) & 1)) * 2560 + (lane >> 4) * 128 + (lane & 7) * 16 + 256 * i);
    const float SC = 0.22360679774997896f * 1.4426950408889634f, ev = (j | rb) == 0 ? -1e9f / 0.22360679774997896f : 0.f;
    const float e4[4] = {ev, ev, ev, ev};
#pragma unroll
    for (int hd = 0; hd < 4; ++hd) mma16(S0[hd], qf[hd], kh[2 * hd], kh[2 * hd + 1], e4);
#pragma unroll
    for (int hd = 0; hd < 4; ++hd) mma8(S0[hd], qs[hd][0], qs[hd][1], kh[8 + (hd >> 1)], S0[hd]);
    const bool up0 = 2 * t > gq, up1 = 2 * t + 1 > gq;
    const uint32_t M = (up0 ? 0xFFFFu : 0u) | (up1 ? 0xFFFF0000u : 0u);
    uint32_t pp[4][2];
    {
      float a[8][2], mx[8];
#pragma unroll
      for (int hd = 0; hd < 4; ++hd) {
        a[2 * hd][0] = up0 ? S0[hd][0] : S1[hd][0];
        a[2 * hd][1] = up1 ? S0[hd][1] : S1[hd][1];
        a[2 * hd + 1][0] = up0 ? S1[hd][2] : S2[hd][2];
        a[2 * hd + 1][1] = up1 ? S1[hd][3] : S2[hd][3];
      }
#pragma unroll
      for (int i = 0; i < 8; ++i) mx[i] = fmaxf(a[i][0], a[i][1]);
#pragma unroll
      for (int s = 1; s < 4; s <<= 1) {
#pragma unroll
        for (int i = 0; i < 8; ++i) mx[i] = fmaxf(mx[i], shx(mx[i], s));
      }
#pragma unroll
      for (int i = 0; i < 8; ++i) {
        const float ms = mx[i] * -SC;
        pp[i >> 1][i & 1] = pack2(ex2(fmaf(a[i][0], SC, ms)), ex2(fmaf(a[i][1], SC, ms)));
      }
    }
    float L[4][4], O[4][3][4];
#pragma unroll
    for (int hd = 0; hd < 4; ++hd) mma8(L[hd], pp[hd][0], pp[hd][1], 0x3F803F80u, z4);
#pragma unroll
    for (int hd = 0; hd < 4; ++hd) {
      const uint32_t p0 = pp[hd][0] & M, p2 = pp[hd][0] & ~M, p3 = pp[hd][1] & M, p5 = pp[hd][1] & ~M;
      const uint32_t z0 = pp[hd][0] & P.zero, z1 = pp[hd][1] & P.zero;
#pragma unroll
      for (int e = 0; e < 3; ++e) {
        const int f = 5 * (hd >> 1) + 2 * (hd & 1) + e;
        mma16(O[hd][e], p0, z0, z1, p5, vv[2 * f], vv[2 * f + 1], z4);
      }
#pragma unroll
      for (int e = 0; e < 3; ++e) mma8(O[hd][e], p2, p3, vl[5 * (hd >> 1) + 2 * (hd & 1) + e], O[hd][e]);
    }
    if (p == 1) bar_arrive<NB_PV, 256>();
    const bool odd = t >> 1;
#pragma unroll
    for (int hp = 0; hp < 2; ++hp) {
      const float (&A)[3][4] = O[2 * hp];
      const float (&B)[3][4] = O[2 * hp + 1];
#pragma unroll
      for (int e = 0; e < 2; ++e) {
        const float ra = rcp(L[2 * hp][2 * e]), rc = rcp(L[2 * hp + 1][2 * e]), rm = odd ? rc : ra;
        uint32_t* const d = &o[0][0] + 10 * hp + e;
        d[0] = pack2(A[0][2 * e] * ra, A[0][2 * e + 1] * ra);
        d[2] = pack2(A[1][2 * e] * ra, A[1][2 * e + 1] * ra);
        d[4] = pack2((odd ? B[0][2 * e] : A[2][2 * e]) * rm, (odd ? B[0][2 * e + 1] : A[2][2 * e + 1]) * rm);
        d[6] = pack2(B[1][2 * e] * rc, B[1][2 * e + 1] * rc);
        d[8] = pack2(B[2][2 * e] * rc, B[2][2 * e + 1] * rc);
      }
      if (hp == 0) {
#pragma unroll
        for (int s = 0; s < 2; ++s) {
          o[s][0] = tag(o[s][0], ep);
          st_rlx4(opub + 256 * s, o[s]);
        }
      }
    }
#pragma unroll
    for (int s = 2; s < 5; ++s) o[s][0] = tag(o[s][0], ep);
  }
  TSTAMP(11);

  float acc[40];
#pragma unroll
  for (int i = 0; i < 40; ++i) asm volatile("" : "=f"(acc[i]));
  uint32_t ga[10], pb[10], uw;
  uint4* const sdst = at<16>(box + M_ST2, 16 * rb + gq);
  const uint32_t prow = sb + OFF_PRM + (lane >> 3) * 16;
  {
    const uint64_t dw = make_desc(sb, 5120, 512, 2);
    const uint4* src[7];
#pragma unroll
    for (int i = 0; i < 7; ++i) src[i] = at<32 * BOX>(opub - 14 * BOX, 7 - g + i + (i >= g));
    uint32_t in[NSET][7][4];
    st_rlx4(opub + 256 * 2, o[2]);
    mbar_wait(bar + 8 * B_WO0, 0);
    if (p == 0) bar_sync<NB_PV, 256>();
#pragma unroll
    for (int i = 0; i < 7; ++i) ld_rlx4(in[0][i], src[i]);
    wg_fence();
    turn_wait(turn);
#pragma unroll
    for (int s = 0; s < 5; ++s) wgmma_n80(acc, o[s], dw + (wo_off(0) + 1024 * s >> 4), s);
    wg_commit();
    turn_pass(turn);
    TSTAMP(12);
#pragma unroll
    for (int s = 0; s < 5; ++s) {
      uint32_t (&cur)[7][4] = in[s % NSET];
      if (s == 0) mbar_wait(bar + 8 * B_WO1, 0);
      else if (NSET == 2) wg_wait();
      if (s || B0) sched_fence(P.zero);
      if ((s == 0 && !B0) || retry<1>(stale<7, 0>(cur, ep), budget)) {
#pragma unroll 1
        do {
#pragma unroll
          for (int i = 0; i < 7; ++i) ld_rlx4(cur[i], src[i] + 256 * s);
        } while (retry<1>(stale<7, 0>(cur, ep), budget));
      }
      TSTAMP(13 + s);
      if (s < 4) {
        if (s > 1 && NSET == 3) asm volatile("wgmma.wait_group.sync.aligned 1;" ::: "memory");
#pragma unroll
        for (int i = 0; i < 7; ++i) ld_rlx4(in[(s + 1) % NSET][i], src[i] + 256 * (s + 1));
      }
      if (s == 0) { st_rlx4(opub + 256 * 3, o[3]); st_rlx4(opub + 256 * 4, o[4]); }
      if (s == FGO_STEP && tid == 128) mbar_arrive(bar + 8 * B_GO);
      wg_fence();
      turn_wait(turn);
#pragma unroll
      for (int i = 0; i < 7; ++i) wgmma_n80(acc, cur[i], dw + (wo_off(i + 1) + 1024 * s >> 4), 1);
      wg_commit();
      if (s < 4 || p == 0) turn_pass(turn);
    }
    mbar_wait(bar + 8 * B_TAB, 1);
    ld_row(ga, prow + R_GA);
    ldsm4(pb, lane & 1 ? prow + R_P : sb + OFF_PRM + R_ONE);
    ldsm4(pb + 4, lane & 1 ? prow + R_P + 64 : sb + OFF_PRM + R_ONE);
    ldsm2(pb + 8, lane & 1 ? prow + R_P + 128 : sb + OFF_PRM + R_ONE);
    uw = tag(lds1(sb + OFF_KEY + 64), ep);
    wg_wait();
  }
  TSTAMP(18);

  uint32_t wf[20][4];
#pragma unroll
  for (int i = 0; i < 80; ++i) asm volatile("" : "=r"(wf[i >> 2][i & 3]));
  const auto load_ffn = [&]() {
    mbar_wait(bar + 8 * B_FFN, 1);
    if (p == 0) {
#pragma unroll
      for (int i = 0; i < 20; ++i)
        ldsm4t(wf[i], sb + OFF_FFN + (lane & 8) * 2560 + (80 * wq + 8 * (lane >> 4) + (lane & 7)) * 64 + (((i & 3) ^ ((lane >> 1) & 3)) << 4) + 1024 * (i >> 2));
    } else {
      const uint32_t kr = ((lane & 7) >> 1) + 4 * (lane >> 4) + 8 * (lane & 1);
#pragma unroll
      for (int i = 0; i < 10; ++i) ldsm4t(wf[i], sb + OFF_FFN + 40960 + kr * 128 + (((2 * wq + ((lane >> 3) & 1)) ^ (kr & 7)) << 4) + 2048 * i);
    }
    TSTAMP(23);
  };
  const uint32_t xt = sb + OFF_X2 + (16 * rb + (lane & 15)) * 160 + (lane >> 4) * 16;
  {
#pragma unroll
    for (int k = 0; k < 20; ++k) xr[k >> 2][k & 3] = fma2(ga[k >> 1], pack2(acc[2 * k], acc[2 * k + 1]), xr[k >> 2][k & 3]);
    float s[4], qlo, qhi;
    row_stats(s, qlo, qhi, xr, pb, gq);
    if (t == gq >> 1) {
      st_rlx4(sdst, u32(s[0]), u32(s[1]), u32(qlo), uw);
      st_rlx4(sdst + 8, u32(s[2]), u32(s[3]), u32(qhi), uw);
    }
    sched_fence(P.zero);
    TSTAMP(19);
#pragma unroll
    for (int s5 = 0; s5 < 5; ++s5) stsm4(xt + 32 * s5, xr[s5]);
    if (WF_EARLY && b < N_FFN) load_ffn();
    uint32_t c1[10], sv[10], gb[10], m[4][4];
    ld_row(c1, prow + R_C1);
    ld_row(sv, prow + R_SB);
    ld_row(gb, prow + R_GB);
    gather_lazy<4, 2 * BOX, 4 * BOX, 3>(m, at<16>(P.sc + M_ST2, (16 * j + rank + 8 * (lane & 1)) * BOX + 16 * rb + (lane >> 1)), ep, budget);
    TSTAMP(20);
#pragma unroll
    for (int e = 0; e < 4; ++e) {
      s[e] = (f32(m[0][e]) + f32(m[1][e])) + (f32(m[2][e]) + f32(m[3][e]));
      s[e] += shx(s[e], 1);
    }
    float mean, rstd;
    const uint32_t nw = norm_word(s[0], s[2], mean, rstd), u = u32(rstd * fmaf(-mean, s[3], s[1]));
    const uint32_t key = ((u ^ ((uint32_t)((int)u >> 31) | 0x80000000u)) | 2047u) ^ (256 * j + 32 * rb + (lane & 30) + rank);
    if (key == __reduce_max_sync(0xFFFFFFFFu, key)) sts2(sb + OFF_KEY + 8 * rb, key, nw);
    bar_arrive<NB_KEY, 288>();
    TSTAMP(21);
    const uint32_t n0 = __shfl_sync(0xFFFFFFFFu, nw, 2 * gq), n1 = __shfl_sync(0xFFFFFFFFu, nw, 2 * gq + 16);
    nrm[0] = dup_hi(n0); nrm[1] = dup_hi(n1); nrm[2] = dup_lo(n0); nrm[3] = dup_lo(n1);
#pragma unroll
    for (int k = 0; k < 20; ++k) {
      uint32_t& x = xr[k >> 2][k & 3];
      x = fma2(gb[k >> 1], fma2(fma2(x, nrm[k & 1], nrm[2 + (k & 1)]), c1[k >> 1], sv[k >> 1]), x);
    }
    bar_sync<NB_PUB, 352>();
#pragma unroll
    for (int s5 = 0; s5 < 5; ++s5) stsm4(xt + (OFF_OUT - OFF_X2) + 32 * s5, xr[s5]);
    asm volatile("fence.proxy.async.shared::cta;" ::: "memory");
    bar_arrive<NB_OUT, 288>();
  }
  TSTAMP(22);
  if (b >= N_FFN) return;

  if (!WF_EARLY) load_ffn();
  if (p == 0) {
    uint32_t m[6][4];
    const uint4* src = at<16>(P.sc + M_CAND, (8 * (gq & 6) + (gq & 1) + 8 * rank + 2 * wq) * BOX + t);
    const uint32_t far = sb + OFF_ACT + (4 * rank + wq) * 128 + gq * 16;
#pragma unroll
    for (int i = 0; i < 24; ++i) asm volatile("" : "=r"(m[i >> 2][i & 3]));
#pragma unroll 1
    for (int pass = DRY; pass < 2; ++pass) {
      if (pass) gather_lazy<6, 64 * BOX, 4, 0>(m, src, ep, budget);
      TSTAMP(24);
      const bool second = m[5][2] > m[4][2];
      const uint32_t wtok = ~__reduce_max_sync(0xFFFFFFFFu, max(m[4][2], m[5][2]));
      float f[4][4];
#pragma unroll
      for (int s = 0; s < 5; ++s) {
        const uint32_t b0 = second ? m[(s & 6) + 1][2 * (s & 1)] : m[s & 6][2 * (s & 1)], b1 = second ? m[(s & 6) + 1][2 * (s & 1) + 1] : m[s & 6][2 * (s & 1) + 1];
#pragma unroll
        for (int mt = 0; mt < 4; ++mt) mma16(f[mt], wf[4 * s + mt], b0, b1, s ? f[mt] : z4);
      }
      const bool e = wtok & 1;
#pragma unroll
      for (int r = 0; r < 2; ++r)
        asm volatile("{.reg .pred p; setp.eq.u32 p, %6, %7;\n"
                     "@p st.async.weak.shared::cluster.mbarrier::complete_tx::bytes.v4.f32 [%0], {%1, %2, %3, %4}, [%5];}"
                     ::"r"(map_to_cta(far, r)), "f"(e ? f[2 * r][1] : f[2 * r][0]), "f"(e ? f[2 * r][3] : f[2 * r][2]),
                       "f"(e ? f[2 * r + 1][1] : f[2 * r + 1][0]), "f"(e ? f[2 * r + 1][3] : f[2 * r + 1][2]), "r"(map_to_cta(bar + 8 * B_ACT, r)),
                       "r"(t + 4 - 4 * pass), "r"((wtok >> 8) & 3) : "memory");
    }
  } else {
    uint4* const ydst = at<16>(box + M_YP, 8 * wq + gq);
#pragma unroll 1
    for (int pass = DRY; pass < 2; ++pass) {
      if (pass) mbar_wait(bar + 8 * B_ACT, 1);
      TSTAMP(24);
      float v[8];
#pragma unroll
      for (int i = 0; i < 8; ++i) v[i] = f32(lds1(sb + OFF_ACT + 128 * i + 4 * lane));
      const float gu = bf_round(((v[0] + v[1]) + (v[2] + v[3])) + ((v[4] + v[5]) + (v[6] + v[7])));
      const float a = bf_round(gu * sigmoid(gu)) * shx(gu, 1);
      const uint32_t aw = pack2(a, shx(a, 2));
      const uint32_t b0 = __shfl_sync(0xFFFFFFFFu, aw, 4 * t), b1 = __shfl_sync(0xFFFFFFFFu, aw, 4 * t + 16);
      const bool odd = gq & 1;
      float y[5][4];
#pragma unroll
      for (int q = 0; q < 5; ++q) mma16(y[q], wf[2 * q], odd ? 0u : b0, odd ? 0u : b1, z4);
#pragma unroll
      for (int q = 0; q < 5; ++q) {
        mma16(y[q], wf[2 * q + 1], odd ? b0 : 0u, odd ? b1 : 0u, y[q]);
        asm volatile("{.reg .pred p; setp.eq.u32 p, %5, 0; @p st.relaxed.gpu.global.v4.u32 [%0], {%1, %2, %3, %4};}"
                     ::"l"(ydst + 32 * q), "r"(tag(u32(y[q][0]), ep)), "r"(u32(y[q][1])), "r"(u32(y[q][2])), "r"(u32(y[q][3])), "r"(t + 1 - pass) : "memory");
      }
    }
  }
  TSTAMP(25);
}

__global__ void __cluster_dims__(2, 1, 1) __launch_bounds__(384, 1) fused_block_kernel(const __grid_constant__ Params P) {
  extern __shared__ __align__(1024) uint8_t sm[];
  const uint32_t sb = (uint32_t)__cvta_generic_to_shared(sm), t0 = clock32();
  const int tid = threadIdx.x, lane = tid & 31, warp = __shfl_sync(0xFFFFFFFFu, tid >> 5, 0);
  const uint32_t bar = sb + OFF_BAR;
  if (warp >= 10 && elect_one()) {
    const uint32_t a = bar + 32 * (11 - warp);
    mbar_init(bar + 8 * warp, 1);
#pragma unroll
    for (int i = 0; i < 4; ++i) mbar_init(a + 8 * i, warp == 10 ? 16 : 1);
    mbar_init(bar + 8 * (warp - 2), warp == 10 ? 8 : 96);
    asm volatile("fence.mbarrier_init.release.cluster;" ::: "memory");
  }
  __syncwarp();
  asm volatile("barrier.cluster.arrive.relaxed.aligned;" ::: "memory");
  if (warp == 11 && elect_one()) {
    asm volatile("prefetch.tensormap [%0];" ::"l"(&P.xa) : "memory");
    asm volatile("prefetch.tensormap [%0];" ::"l"(&P.w0) : "memory");
    asm volatile("prefetch.tensormap [%0];" ::"l"(&P.w1) : "memory");
  }
  uint32_t key = blockIdx.x;
  asm("mov.u32 %0, %%smid;" : "=r"(key));
  const int c = key >> 1, rank = blockIdx.x & 1, kb = 2 * (c < 32 ? (c & 16) + 2 * (c & 7) + ((c >> 3) & 1) : c) + rank;
  const bool gemv = warp < 10 && c < 40;
  const uint32_t wt = sb + 3 * STAGE + 2048 * warp;
  uint32_t cv = 0;
  if (gemv) {
    const int row = 320 * rank + 32 * warp;
    const __nv_bfloat16* src = at<2>(P.wmod, (row + (lane >> 2)) * 3840 + 16 * (kb - rank) + 8 * (lane & 3));
#pragma unroll
    for (int i = 0; i < 4; ++i)
      asm volatile("cp.async.cg.shared.global.L2::128B [%0], [%1], 16;" ::"r"(wt + 512 * i + 16 * (lane ^ (lane >> 3))), "l"(src + i * 8 * 3840) : "memory");
    asm volatile("ld.global.nc.u16 %0, [%1];" : "=r"(cv) : "l"(at<2>(P.c, row + lane)));
  }
  TSTAMP(26);
  const int q7 = ((c - 32) * 37) >> 8, pr = c < 32 ? 8 * (c & 7) + (c >> 3) : c < 60 ? 8 * c - 55 * q7 - 244 : c - 58, b = 2 * pr + rank;
  if (BY_SM && (c >> 1) == 30) {
    wait_until(t0 + 4000);
    return;
  }
  uint4* const box = P.sc + b * BOX;
  int budget = SPIN_LIMIT;
  uint32_t e0 = 0;
  TSTAMP(27);
  if (warp == 11) {
    asm volatile("barrier.cluster.wait.aligned;" ::: "memory");
    TSTAMP(28);
#pragma unroll 1
    for (int st = 0; st < EARLY; ++st) {
      wait_until(t0 + S0_AT + st * S_GAP);
      if (elect_one()) load_stage(P, sb, st, b >> 4, pr & 7, rank);
    }
  } else {
    if (warp != 10) e0 = ld_rlx1(at<4>(box + M_EPOCH, lane));
    if (warp == 10) {
      uint4* const dst = at<16>(P.sc, kb * BOX + lane);
      if (c < 40) st_rlx4(dst, 0u, 0u, 0u, 0u);
      st_rlx1(at<4>(box + M_ST1, lane), 0u);
      asm volatile("barrier.cluster.wait.aligned;" ::: "memory");
      wait_until(t0 + XS_AT);
      if (elect_one()) {
        mbar_expect_tx(bar + 8 * B_GO, c < 40 ? 1280 : 0);
        mbar_expect_tx(bar + 8 * B_XS, 20480);
        bulk_load(sb + OFF_XS, P.x + b * 10240, 20480, bar + 8 * B_XS);
      }
      TSTAMP(28);
      e0 = ld_rlx1(at<4>(box + M_EPOCH, lane));
      TALIGN(0);
      if (c < 40) {
        const uint32_t ep = next_epoch(e0);
        mbar_wait(bar + 8 * B_GO, 0);
        TSTAMP(1);
        float v[10];
#pragma unroll
        for (int i = 0; i < 10; ++i) v[i] = f32(lds1(sb + OFF_RED + 128 * i + 4 * lane));
        float s = ((v[0] + v[1]) + (v[2] + v[3])) + ((v[4] + v[5]) + (v[6] + v[7])) + (v[8] + v[9]);
        s += shx(s, 16);
        const uint32_t w = fma2(pack2(s, shx(s, 1)), 0x3F803F80u, kb < 40 ? 0u : 0x3F803F80u);
        st_rlx4(dst, __shfl_sync(0xFFFFFFFFu, w, 2 * (lane & 3)), __shfl_sync(0xFFFFFFFFu, w, 2 * (lane & 3) + 8), ep, ep);
        TSTAMP(2);
      }
    } else if (gemv) {
      const float x = bf_lo(cv), s = x * sigmoid(x);
      const uint32_t sw = pack2(s, shx(s, 1));
      uint32_t bw[4], a[4][4];
#pragma unroll
      for (int i = 0; i < 4; ++i) bw[i] = __shfl_sync(0xFFFFFFFFu, sw, 8 * i + 2 * (lane & 3));
      const uint32_t far = map_to_cta(sb, (lane >> 1) & 1), dst = far + OFF_RED + 128 * warp + 64 * rank + 32 * (lane & 1) + (lane & 28);
      const uint32_t la = wt + (lane >> 4) * 512 + (lane & 7) * 64 + ((((lane >> 3) & 1) ^ ((lane >> 1) & 3)) << 4);
      asm volatile("barrier.cluster.wait.aligned;" ::: "memory");
      sched_fence(P.zero);
      asm volatile("cp.async.wait_all;" ::: "memory");
      __syncwarp();
      TSTAMP(28);
#pragma unroll
      for (int i = 0; i < 4; ++i) ldsm4t(a[i], (la ^ (32 * (i & 1))) + (i >> 1) * 1024);
      float d[2][4];
      const float z4[4] = {0.f, 0.f, 0.f, 0.f};
#pragma unroll
      for (int i = 0; i < 4; ++i) mma16(d[i & 1], a[i], bw[i & 2], bw[(i & 2) + 1], i < 2 ? z4 : d[i & 1]);
      const float v = lane & 2 ? (lane & 1 ? d[1][2] : d[1][0]) : (lane & 1 ? d[0][2] : d[0][0]);
      asm volatile("st.async.weak.shared::cluster.mbarrier::complete_tx::bytes.f32 [%0], %1, [%2];" ::"r"(dst), "f"(v), "r"(far + OFF_BAR + 8 * B_GO) : "memory");
      TSTAMP(1);
    } else {
      asm volatile("barrier.cluster.wait.aligned;" ::: "memory");
    }
  }
  if (warp >= 8) {
    asm volatile("setmaxnreg.dec.sync.aligned.u32 56;");
    if (warp == 11) {
      wait_until(t0 + WPF_AT);
      if (elect_one()) bulk_prefetch(P.wqkv + (128 + 4 * b) * 1920, 15360);
      run_producer(P, sm, sb, b);
    } else {
      run_helper(P, sm, sb, b, warp - 8, next_epoch(e0), budget, t0 + POLL_AT);
    }
    TDUMP();
  } else {
    run_consumer(P, sm, sb, b, warp, next_epoch(e0), budget);
    TDUMP();
  }
}

typedef CUresult (*EncodeFn)(CUtensorMap*, CUtensorMapDataType, cuuint32_t, void*, const cuuint64_t*, const cuuint64_t*, const cuuint32_t*,
                             const cuuint32_t*, CUtensorMapInterleave, CUtensorMapSwizzle, CUtensorMapL2promotion, CUtensorMapFloatOOBfill);

void encode(EncodeFn fn, CUtensorMap* m, const void* base, int rank, const cuuint64_t* dims, const cuuint64_t* strides, const cuuint32_t* box,
            CUtensorMapSwizzle sw) {
  const cuuint32_t es[3] = {1, 1, 1};
  fn(m, CU_TENSOR_MAP_DATA_TYPE_BFLOAT16, rank, const_cast<void*>(base), dims, strides, box, es, CU_TENSOR_MAP_INTERLEAVE_NONE, sw,
     CU_TENSOR_MAP_L2_PROMOTION_L2_128B, CU_TENSOR_MAP_FLOAT_OOB_FILL_NONE);
}

}

extern "C" void kernel_launch(void* const* d_in, const int* in_sizes, int n_in, void* d_out, int out_size) {
  (void)in_sizes; (void)n_in; (void)out_size;
  static EncodeFn fn = nullptr;
  static void* scratch = nullptr;
  if (!fn) {
    void* f = nullptr;
    cudaDriverEntryPointQueryResult q;
    cudaGetDriverEntryPoint("cuTensorMapEncodeTiled", &f, cudaEnableDefault, &q);
    fn = (EncodeFn)f;
    cudaFuncSetAttribute(fused_block_kernel, cudaFuncAttributeMaxDynamicSharedMemorySize, SMEM_BYTES);
    cudaGetSymbolAddress(&scratch, g_scratch);
  }
  Params P;
  P.sc = (uint4*)scratch;
  P.zero = 0;
  const cuuint64_t xd[2] = {1280, 1024}, xs[1] = {2560};
  const cuuint32_t xb[2] = {64, 128};
  encode(fn, &P.xa, d_in[0], 2, xd, xs, xb, CU_TENSOR_MAP_SWIZZLE_128B);
  const cuuint32_t ob[2] = {80, 16};
  encode(fn, &P.om, d_out, 2, xd, xs, ob, CU_TENSOR_MAP_SWIZZLE_NONE);
  const cuuint64_t wd3[3] = {640, 640, 3}, ws3[2] = {3840, 1280};
  const cuuint32_t w0b[3] = {64, 32, 3}, w1b[3] = {16, 32, 3};
  encode(fn, &P.w0, d_in[1], 3, wd3, ws3, w0b, CU_TENSOR_MAP_SWIZZLE_128B);
  encode(fn, &P.w1, d_in[1], 3, wd3, ws3, w1b, CU_TENSOR_MAP_SWIZZLE_32B);
  const cuuint64_t md[2] = {3840, 640}, ms[1] = {7680};
  const cuuint32_t mb[2] = {80, 160};
  encode(fn, &P.wm, d_in[9], 2, md, ms, mb, CU_TENSOR_MAP_SWIZZLE_NONE);
  const cuuint64_t od3[3] = {608, 640, 2}, os3[2] = {1280, 64}, od2[2] = {640, 640}, os2[1] = {1280};
  const cuuint32_t oab[3] = {32, 80, 2}, obb[2] = {16, 80};
  encode(fn, &P.woa, d_in[2], 3, od3, os3, oab, CU_TENSOR_MAP_SWIZZLE_64B);
  encode(fn, &P.wob, d_in[2], 2, od2, os2, obb, CU_TENSOR_MAP_SWIZZLE_64B);
  const cuuint64_t gd[3] = {1728, 160, 4}, gs[2] = {3456, 160 * 3456}, dd[3] = {64, 1728, 10}, ds[2] = {1280, 128};
  const cuuint32_t gb[3] = {32, 160, 1}, db[3] = {64, 16, 10}, tgb[3] = {8, 160, 1}, tdb[3] = {8, 16, 10};
  encode(fn, &P.wg, d_in[5], 3, gd, gs, gb, CU_TENSOR_MAP_SWIZZLE_64B);
  encode(fn, &P.wu, d_in[6], 3, gd, gs, gb, CU_TENSOR_MAP_SWIZZLE_64B);
  encode(fn, &P.wd, d_in[7], 3, dd, ds, db, CU_TENSOR_MAP_SWIZZLE_128B);
  encode(fn, &P.tg, d_in[5], 3, gd, gs, tgb, CU_TENSOR_MAP_SWIZZLE_NONE);
  encode(fn, &P.tu, d_in[6], 3, gd, gs, tgb, CU_TENSOR_MAP_SWIZZLE_NONE);
  encode(fn, &P.td, d_in[7], 3, dd, ds, tdb, CU_TENSOR_MAP_SWIZZLE_NONE);
  P.x = (const __nv_bfloat16*)d_in[0];
  P.wqkv = (const __nv_bfloat16*)d_in[1];
  P.wr = (const __nv_bfloat16*)d_in[4];
  P.wo = (const __nv_bfloat16*)d_in[2];
  P.wgate = (const __nv_bfloat16*)d_in[5];
  P.wup = (const __nv_bfloat16*)d_in[6];
  P.wdown = (const __nv_bfloat16*)d_in[7];
  P.c = (const __nv_bfloat16*)d_in[8];
  P.wmod = (const __nv_bfloat16*)d_in[9];
  P.out = (__nv_bfloat16*)d_out;
  fused_block_kernel<<<BY_SM ? 132 : 128, 384, SMEM_BYTES>>>(P);
}
```

```cpp
#include <cuda_runtime.h>
#include <cuda.h>
#include <cuda_bf16.h>
#include <stdint.h>

namespace {

constexpr int STAGE_A = 16384, STAGE_B0 = 24576, STAGE_B1 = 6144, STAGE = STAGE_A + STAGE_B0 + STAGE_B1;
constexpr int WO = 15360;
constexpr int OFF_FFN = 4 * WO, OFF_LM = 2 * STAGE, OFF_X2 = 4 * STAGE, OFF_OUT = 0;
constexpr int OFF_H = 4 * STAGE, OFF_L = OFF_H + 9 * 2560, OFF_XS = OFF_H, OFF_RED = OFF_L, OFF_SINK = OFF_L + 10240;
constexpr int OFF_C1 = 225280, OFF_ACT = OFF_C1, OFF_PRM = OFF_C1 + 2560, OFF_SILU = OFF_PRM + 1600;
constexpr int OFF_KEY = OFF_SILU + 320, OFF_BAR = OFF_KEY + 128, OFF_TIME = OFF_BAR + 256, SMEM_BYTES = OFF_TIME + 1536;
static_assert(OFF_H % 512 == 0, "lane bits of the halo address");
static_assert(SMEM_BYTES <= 232448 && OFF_BAR % 64 == 0, "smem");
enum { R_GA = 0, R_SB = 160, R_C1 = 320, R_GB = 480, R_FIN = 640, R_P = 800 + R_C1, R_ONE = 704 };

enum { B_FULL = 0, B_EMPTY = 4, B_HALO = 8, B_TAB = 9, B_GO = 10, B_XS = 11, B_ACT = B_FULL, B_FFN = B_FULL + 1, B_WO0 = B_FULL + 2, B_WO1 = B_FULL + 3 };
enum { NB_PV = 1, NB_TURN = 2, NB_KEY = 4, NB_HELP = 6, NB_HALO = 7, NB_PUB = 8, NB_GO = 9, NB_LM = 10, NB_OUT = 11, NB_WIN = 13, NB_YP = 14 };

enum { M_EARLY = 0, M_ST1 = 32, M_EPOCH = 40, M_HALO = 48, M_ST2 = 208, M_CAND = 336, M_LATE = 368, M_YP = 400, M_O = 560, BOX = 1840 };
__device__ uint4 g_scratch[128 * BOX];

constexpr int N_FFN = 108;
#define XS_AT 1200
#define S0_AT 0
#define WPF_AT 4500
#define LATE_GAP 1500
#define PUB 3
#define NOPEN 768
#define NSET 3
#define TOUCH_MAP 0xFF2F1F0Fu
#define LMPF_AT 4
#define OPEN_GAP 0
#define WPF0_AT WPF_AT
#define S2_AT 0
#define GO_ST 2
#define FFN_GAP 400
#define DRY 1
#define OUT_AT 600
#define WF_EARLY 0
#define XS_POS 0
#define NO_TPF 0
#define B0 2
#define HALO3 1
#define HALO_GAP 400
#define PASS_AT 5
#define PASS0 2
#define PASS1 5
#define XS_HI XS_AT
#define LSU_TOUCH 1
#define TOUCH_AT 1000
#define TOUCH_GAP 900
#define NAP 40
#define PRM_EARLY 0
#define ST2_GAP 100
#define OUT2_AT 0
#define PUB_FENCE 1
#define PACK_FIRST 2
#define YP_GAP 200
#define CAND_GAP 0
#define POLL_AT 3400
#define S_GAP 1200
#define EARLY 2
#define OUT_GAP 200
#define BY_SM 1
#define FGO_STEP 2
constexpr int SPIN_LIMIT = 1 << 16;

struct Params {
  const __nv_bfloat16 *wmod, *c, *x;
  uint4* sc;
  uint32_t zero;
  const __nv_bfloat16 *wqkv, *wr, *wo, *wgate, *wup, *wdown;
  __nv_bfloat16* out;
  CUtensorMap xa, w0, w1, wm, woa, wob, wg, wu, wd, tg, tu, td, om;
};

__device__ __forceinline__ uint32_t clock32() {
  uint32_t c;
  asm volatile("mov.u32 %0, %%clock;" : "=r"(c));
  return c;
}
#define TSTAMP(i) do { } while (0)
#define TDUMP() do { } while (0)
#define TALIGN(k) do { } while (0)

__device__ __forceinline__ void mbar_init(uint32_t b, uint32_t c) { asm volatile("mbarrier.init.shared::cta.b64 [%0], %1;" ::"r"(b), "r"(c) : "memory"); }
__device__ __forceinline__ void mbar_expect_tx(uint32_t b, uint32_t n) { asm volatile("mbarrier.arrive.expect_tx.shared::cta.b64 _, [%0], %1;" ::"r"(b), "r"(n) : "memory"); }
__device__ __forceinline__ void mbar_arrive(uint32_t b) { asm volatile("mbarrier.arrive.shared::cta.b64 _, [%0];" ::"r"(b) : "memory"); }
__device__ __forceinline__ uint32_t map_to_cta(uint32_t a, uint32_t rank) {
  uint32_t r;
  asm("mapa.shared::cluster.u32 %0, %1, %2;" : "=r"(r) : "r"(a), "r"(rank));
  return r;
}
__device__ __forceinline__ void mbar_arrive_cluster(uint32_t b) { asm volatile("mbarrier.arrive.shared::cluster.b64 _, [%0];" ::"r"(b) : "memory"); }
__device__ __forceinline__ void mbar_wait(uint32_t b, uint32_t ph) {
  asm volatile("{.reg .pred p;\n"
               "RETRY: mbarrier.try_wait.parity.shared::cta.b64 p, [%0], %1;\n"
               "@!p bra RETRY;}" ::"r"(b), "r"(ph) : "memory");
}
__device__ __forceinline__ bool elect_one() {
  uint32_t r;
  asm volatile("{.reg .pred p; elect.sync _|p, 0xFFFFFFFF; selp.u32 %0, 1, 0, p;}" : "=r"(r));
  return r;
}
template <int ID, int N> __device__ __forceinline__ void bar_sync() { asm volatile("bar.sync %0, %1;" ::"n"(ID), "n"(N) : "memory"); }
template <int ID, int N> __device__ __forceinline__ void bar_arrive() { asm volatile("bar.arrive %0, %1;" ::"n"(ID), "n"(N) : "memory"); }
__device__ __forceinline__ void turn_wait(uint32_t id) { asm volatile("bar.sync %0, 256;" ::"r"(id) : "memory"); }
__device__ __forceinline__ void turn_pass(uint32_t id) { asm volatile("bar.arrive %0, 256;" ::"r"(id) : "memory"); }
__device__ __forceinline__ void tma2(uint32_t dst, const CUtensorMap* m, uint32_t bar, int c0, int c1) {
  asm volatile("cp.async.bulk.tensor.2d.shared::cluster.global.mbarrier::complete_tx::bytes [%0], [%1, {%3, %4}], [%2];" ::"r"(dst), "l"(m), "r"(bar), "r"(c0), "r"(c1) : "memory");
}
__device__ __forceinline__ void tma3(uint32_t dst, const CUtensorMap* m, uint32_t bar, int c0, int c1, int c2) {
  asm volatile("cp.async.bulk.tensor.3d.shared::cluster.global.mbarrier::complete_tx::bytes [%0], [%1, {%3, %4, %5}], [%2];" ::"r"(dst), "l"(m), "r"(bar), "r"(c0), "r"(c1), "r"(c2) : "memory");
}
__device__ __forceinline__ void tma2_both(uint32_t dst, const CUtensorMap* m, uint32_t bar, int c0, int c1) {
  asm volatile("cp.async.bulk.tensor.2d.shared::cluster.global.mbarrier::complete_tx::bytes.multicast::cluster [%0], [%1, {%3, %4}], [%2], %5;"
               ::"r"(dst), "l"(m), "r"(bar), "r"(c0), "r"(c1), "h"((uint16_t)3) : "memory");
}
__device__ __forceinline__ void tma3_both(uint32_t dst, const CUtensorMap* m, uint32_t bar, int c0, int c1, int c2) {
  asm volatile("cp.async.bulk.tensor.3d.shared::cluster.global.mbarrier::complete_tx::bytes.multicast::cluster [%0], [%1, {%3, %4, %5}], [%2], %6;"
               ::"r"(dst), "l"(m), "r"(bar), "r"(c0), "r"(c1), "r"(c2), "h"((uint16_t)3) : "memory");
}
__device__ __forceinline__ void bulk_prefetch(const void* src, uint32_t bytes) {
  asm volatile("cp.async.bulk.prefetch.L2.global [%0], %1;" ::"l"(src), "r"(bytes) : "memory");
}
__device__ __forceinline__ void bulk_load(uint32_t dst, const void* src, uint32_t bytes, uint32_t bar) {
  asm volatile("cp.async.bulk.shared::cluster.global.mbarrier::complete_tx::bytes [%0], [%1], %2, [%3];" ::"r"(dst), "l"(src), "r"(bytes), "r"(bar) : "memory");
}
__device__ __forceinline__ void wg_fence() { asm volatile("wgmma.fence.sync.aligned;" ::: "memory"); }
__device__ __forceinline__ void wg_commit() { asm volatile("wgmma.commit_group.sync.aligned;" ::: "memory"); }
__device__ __forceinline__ void wg_wait() { asm volatile("wgmma.wait_group.sync.aligned 0;" ::: "memory"); }
__device__ __forceinline__ uint64_t make_desc(uint32_t addr, uint32_t lbo, uint32_t sbo, uint32_t mode) {
  return (uint64_t)((addr & 0x3FFFF) >> 4) | ((uint64_t)(lbo >> 4) << 16) | ((uint64_t)(sbo >> 4) << 32) | ((uint64_t)mode << 62);
}
__device__ __forceinline__ void ldsm4(uint32_t& r0, uint32_t& r1, uint32_t& r2, uint32_t& r3, uint32_t a) {
  asm volatile("ldmatrix.sync.aligned.m8n8.x4.shared.b16 {%0, %1, %2, %3}, [%4];" : "=r"(r0), "=r"(r1), "=r"(r2), "=r"(r3) : "r"(a) : "memory");
}
__device__ __forceinline__ void ldsm4(uint32_t* r, uint32_t a) { ldsm4(r[0], r[1], r[2], r[3], a); }
__device__ __forceinline__ void ldsm2(uint32_t* r, uint32_t a) {
  asm volatile("ldmatrix.sync.aligned.m8n8.x2.shared.b16 {%0, %1}, [%2];" : "=r"(r[0]), "=r"(r[1]) : "r"(a) : "memory");
}
__device__ __forceinline__ void ldsm4t(uint32_t* r, uint32_t a) {
  asm volatile("ldmatrix.sync.aligned.m8n8.x4.trans.shared.b16 {%0, %1, %2, %3}, [%4];" : "=r"(r[0]), "=r"(r[1]), "=r"(r[2]), "=r"(r[3]) : "r"(a) : "memory");
}
__device__ __forceinline__ void ldsm2t(uint32_t* r, uint32_t a) {
  asm volatile("ldmatrix.sync.aligned.m8n8.x2.trans.shared.b16 {%0, %1}, [%2];" : "=r"(r[0]), "=r"(r[1]) : "r"(a) : "memory");
}
__device__ __forceinline__ void ld_row(uint32_t (&r)[10], uint32_t a) {
  ldsm4(r, a);
  ldsm4(r + 4, a + 64);
  ldsm2(r + 8, a + 128);
}
__device__ __forceinline__ void stsm4(uint32_t a, const uint32_t* r) {
  asm volatile("stmatrix.sync.aligned.m8n8.x4.shared.b16 [%0], {%1, %2, %3, %4};" ::"r"(a), "r"(r[0]), "r"(r[1]), "r"(r[2]), "r"(r[3]) : "memory");
}
__device__ __forceinline__ void stsm2(uint32_t a, const uint32_t* r) {
  asm volatile("stmatrix.sync.aligned.m8n8.x2.shared.b16 [%0], {%1, %2};" ::"r"(a), "r"(r[0]), "r"(r[1]) : "memory");
}
__device__ __forceinline__ void lds4(uint32_t* r, uint32_t a) {
  asm volatile("ld.shared.v4.u32 {%0, %1, %2, %3}, [%4];" : "=r"(r[0]), "=r"(r[1]), "=r"(r[2]), "=r"(r[3]) : "r"(a) : "memory");
}
__device__ __forceinline__ uint32_t lds1(uint32_t a) {
  uint32_t v;
  asm volatile("ld.shared.u32 %0, [%1];" : "=r"(v) : "r"(a) : "memory");
  return v;
}
__device__ __forceinline__ void sts1(uint32_t a, uint32_t v) { asm volatile("st.shared.u32 [%0], %1;" ::"r"(a), "r"(v) : "memory"); }
__device__ __forceinline__ void sts2(uint32_t a, uint32_t v0, uint32_t v1) { asm volatile("st.shared.v2.u32 [%0], {%1, %2};" ::"r"(a), "r"(v0), "r"(v1) : "memory"); }
__device__ __forceinline__ void mma16(float (&d)[4], uint32_t a0, uint32_t a1, uint32_t a2, uint32_t a3, uint32_t b0, uint32_t b1, const float* c) {
  asm volatile("mma.sync.aligned.m16n8k16.row.col.f32.bf16.bf16.f32 {%0, %1, %2, %3}, {%4, %5, %6, %7}, {%8, %9}, {%10, %11, %12, %13};"
               : "=f"(d[0]), "=f"(d[1]), "=f"(d[2]), "=f"(d[3])
               : "r"(a0), "r"(a1), "r"(a2), "r"(a3), "r"(b0), "r"(b1), "f"(c[0]), "f"(c[1]), "f"(c[2]), "f"(c[3]));
}
__device__ __forceinline__ void mma16(float (&d)[4], const uint32_t* a, uint32_t b0, uint32_t b1, const float* c) { mma16(d, a[0], a[1], a[2], a[3], b0, b1, c); }
__device__ __forceinline__ void mma8(float (&d)[4], uint32_t a0, uint32_t a1, uint32_t b0, const float* c) {
  asm volatile("mma.sync.aligned.m16n8k8.row.col.f32.bf16.bf16.f32 {%0, %1, %2, %3}, {%4, %5}, {%6}, {%7, %8, %9, %10};"
               : "=f"(d[0]), "=f"(d[1]), "=f"(d[2]), "=f"(d[3]) : "r"(a0), "r"(a1), "r"(b0), "f"(c[0]), "f"(c[1]), "f"(c[2]), "f"(c[3]));
}
__device__ __forceinline__ uint32_t pack2(float lo, float hi) {
  uint32_t r;
  asm volatile("cvt.rn.bf16x2.f32 %0, %1, %2;" : "=r"(r) : "f"(hi), "f"(lo));
  return r;
}
__device__ __forceinline__ float bf_lo(uint32_t w) { return __uint_as_float(w << 16); }
__device__ __forceinline__ float bf_hi(uint32_t w) { return __uint_as_float(w & 0xFFFF0000u); }
__device__ __forceinline__ float bf_round(float v) { return __uint_as_float(pack2(0.f, v)); }
__device__ __forceinline__ uint32_t fma2(uint32_t a, uint32_t b, uint32_t c) {
  uint32_t r;
  asm("fma.rn.bf16x2 %0, %1, %2, %3;" : "=r"(r) : "r"(a), "r"(b), "r"(c));
  return r;
}
__device__ __forceinline__ float ex2(float v) {
  float r;
  asm("ex2.approx.ftz.f32 %0, %1;" : "=f"(r) : "f"(v));
  return r;
}
__device__ __forceinline__ float rcp(float v) {
  float r;
  asm("rcp.approx.ftz.f32 %0, %1;" : "=f"(r) : "f"(v));
  return r;
}
__device__ __forceinline__ float rsq(float v) {
  float r;
  asm("rsqrt.approx.ftz.f32 %0, %1;" : "=f"(r) : "f"(v));
  return r;
}
__device__ __forceinline__ float sigmoid(float v) { return rcp(1.f + ex2(v * -1.4426950408889634f)); }
__device__ __forceinline__ float f32(uint32_t v) { return __uint_as_float(v); }
__device__ __forceinline__ uint32_t u32(float v) { return __float_as_uint(v); }
__device__ __forceinline__ void ld_rlx4(uint32_t* v, const void* p) {
  asm volatile("{.reg .b128 q; ld.relaxed.gpu.global.b128 q, [%4]; mov.b128 {%0, %1, %2, %3}, q;}" : "=r"(v[0]), "=r"(v[1]), "=r"(v[2]), "=r"(v[3]) : "l"(p) : "memory");
}
__device__ __forceinline__ void ld_rlx2(uint32_t* v, const void* p) {
  asm volatile("{.reg .b64 q; ld.relaxed.gpu.global.b64 q, [%2]; mov.b64 {%0, %1}, q;}" : "=r"(v[0]), "=r"(v[1]) : "l"(p) : "memory");
}
__device__ __forceinline__ uint32_t ld_rlx1(const void* p) {
  uint32_t v;
  asm volatile("ld.relaxed.gpu.global.u32 %0, [%1];" : "=r"(v) : "l"(p) : "memory");
  return v;
}
__device__ __forceinline__ void st_rlx4(void* p, uint32_t a, uint32_t b, uint32_t c, uint32_t d) {
  asm volatile("{.reg .b128 q; mov.b128 q, {%1, %2, %3, %4}; st.relaxed.gpu.global.b128 [%0], q;}" ::"l"(p), "r"(a), "r"(b), "r"(c), "r"(d) : "memory");
}
__device__ __forceinline__ void st_rlx4(void* p, const uint32_t* v) { st_rlx4(p, v[0], v[1], v[2], v[3]); }
__device__ __forceinline__ void st_rlx2(void* p, uint32_t a, uint32_t b) { asm volatile("{.reg .b64 q; mov.b64 q, {%1, %2}; st.relaxed.gpu.global.b64 [%0], q;}" ::"l"(p), "r"(a), "r"(b) : "memory"); }
__device__ __forceinline__ void st_rlx1(void* p, uint32_t v) { asm volatile("st.relaxed.gpu.global.u32 [%0], %1;" ::"l"(p), "r"(v) : "memory"); }
template <int LUT> __device__ __forceinline__ uint32_t lop3(uint32_t a, uint32_t b, uint32_t c) {
  uint32_t r;
  asm volatile("lop3.b32 %0, %1, %2, %3, %4;" : "=r"(r) : "r"(a), "r"(b), "r"(c), "n"(LUT));
  return r;
}
__device__ __forceinline__ uint32_t tag(uint32_t w, uint32_t ep) { return lop3<0xD8>(w, ep, 1u); }
__device__ __forceinline__ uint32_t neq2(uint32_t a, uint32_t b, uint32_t e) { return lop3<0x7E>(a, b, e); }
__device__ __forceinline__ uint32_t next_epoch(uint32_t e) {
  asm volatile("add.u32 %0, %0, 1;" : "+r"(e));
  return e;
}
__device__ __forceinline__ void sched_fence(uint32_t zero) {
  asm volatile("{.reg .pred p; setp.ne.u32 p, %0, 0;\nSPIN: pmevent 0; @p bra.uni SPIN;}" ::"r"(zero) : "memory");
}
__device__ __forceinline__ int pick(bool c, int a, int b) {
  int r;
  asm("{.reg .pred p; setp.ne.u32 p, %1, 0; selp.b32 %0, %2, %3, p;}" : "=r"(r) : "r"((uint32_t)c), "r"(a), "r"(b));
  return r;
}
__device__ __forceinline__ uint32_t keep(uint32_t v) { return __shfl_xor_sync(0xFFFFFFFFu, v, 2); }
__device__ __forceinline__ void wait_until(uint32_t t) {
  while ((int)(clock32() - t) < 0) {
    asm volatile("nanosleep.u32 %0;" ::"n"(NAP));
  }
}
__device__ __forceinline__ float shx(float v, int o) { return __shfl_xor_sync(0xFFFFFFFFu, v, o); }
template <int SCALE, class T> __device__ __forceinline__ T* at(T* base, uint32_t i) {
  T* r;
  asm volatile("mad.wide.u32 %0, %1, %2, %3;" : "=l"(r) : "r"(i), "n"(SCALE), "l"(base));
  return r;
}
template <uint32_t MASK> __device__ __forceinline__ bool retry(uint32_t bad, int& budget) {
  uint32_t r;
  asm volatile("{.reg .pred p, q; .reg .b32 t; add.s32 %1, %1, -1; setp.gt.s32 q, %1, 0; and.b32 t, %2, %3; setp.ne.and.u32 p, t, 0, q;\n"
               "vote.sync.any.pred p, p, 0xFFFFFFFF; selp.u32 %0, 1, 0, p;}" : "=r"(r), "+r"(budget) : "r"(bad), "n"(MASK));
  return r;
}
template <int N, int W> __device__ __forceinline__ uint32_t stale(const uint32_t (*v)[4], uint32_t ep) {
  uint32_t bad = neq2(v[0][W], v[N > 1][W], ep);
#pragma unroll
  for (int i = 2; i < N; i += 2) bad |= neq2(v[i][W], v[i + 1 < N ? i + 1 : i][W], ep);
  return bad;
}
__device__ __forceinline__ void ld_rlx4_stale(uint32_t* v, const void* p, uint32_t w, uint32_t ep) {
  asm volatile("{.reg .b128 q; .reg .pred p; .reg .b32 t; lop3.b32 t, %5, %6, 1, 0x28; setp.ne.u32 p, t, 0; mov.b128 q, {%0, %1, %2, %3};\n"
               "@p ld.relaxed.gpu.global.b128 q, [%4]; mov.b128 {%0, %1, %2, %3}, q;}"
               : "+r"(v[0]), "+r"(v[1]), "+r"(v[2]), "+r"(v[3]) : "l"(p), "r"(w), "r"(ep) : "memory");
}
template <int N, int S0, int S1, int W> __device__ __forceinline__ void gather_lazy(uint32_t (*v)[4], const uint4* p, uint32_t ep, int& budget, bool skip_last = false) {
#pragma unroll
  for (int i = 0; i < 4 * N; ++i) {
    if ((i & 3) == W) v[i >> 2][W] = N == 7 && i >= 24 && skip_last ? ep & 1u : ~ep;
    else if (N == 7 && i >= 24) v[6][i & 3] = 0;
    else asm volatile("" : "=r"(v[i >> 2][i & 3]));
  }
#pragma unroll 1
  do {
#pragma unroll
    for (int i = 0; i < N; ++i) ld_rlx4_stale(v[i], p + (i & 1) * S0 + (i >> 1) * S1, v[i][W], ep);
  } while (retry<1>(stale<N, W>(v, ep), budget));
}
template <int N, int STRIDE, int W> __device__ __forceinline__ void gather(uint32_t (*v)[4], const uint4* p, uint32_t ep, int& budget) {
#pragma unroll 1
  do {
#pragma unroll
    for (int i = 0; i < N; ++i) ld_rlx4(v[i], p + i * STRIDE);
  } while (retry<1>(stale<N, W>(v, ep), budget));
}
__device__ __forceinline__ void row_stats(float (&s)[4], float& qlo, float& qhi, const uint32_t (&x)[5][4], const uint32_t (&b)[10], int gq) {
  const float z[4] = {0.f, 0.f, 0.f, 0.f};
  float q[4][4];
#pragma unroll
  for (int i = 0; i < 5; ++i) {
    mma16(s, x[i], b[2 * i], b[2 * i + 1], i ? s : z);
#pragma unroll
    for (int e = 0; e < 4; ++e) mma8(q[e], x[i][e & 2], x[i][(e & 2) + 1], x[i][e], i ? q[e] : z);
  }
  const bool odd = gq & 1;
  qlo = (odd ? q[0][1] : q[0][0]) + (odd ? q[2][1] : q[2][0]);
  qhi = (odd ? q[1][3] : q[1][2]) + (odd ? q[3][3] : q[3][2]);
}
__device__ __forceinline__ uint32_t norm_word(float s, float q, float& mean, float& rstd) {
  mean = s * (1.f / 640.f);
  rstd = rsq(fmaxf(fmaf(q, 1.f / 640.f, -mean * mean), 0.f) + 1e-5f);
  return pack2(-mean * bf_round(rstd), rstd);
}
__device__ __forceinline__ uint32_t dup_lo(uint32_t w) { return __byte_perm(w, 0u, 0x1010); }
__device__ __forceinline__ uint32_t dup_hi(uint32_t w) { return __byte_perm(w, 0u, 0x3232); }

__device__ __forceinline__ void wgmma_n192(float (&d)[96], const uint32_t (&a)[4], uint64_t db, int add) {
  asm volatile("{.reg .pred p; setp.ne.b32 p, %101, 0; wgmma.mma_async.sync.aligned.m64n192k16.f32.bf16.bf16 "
    "{%0, %1, %2, %3, %4, %5, %6, %7, %8, %9, %10, %11, %12, %13, %14, %15, "
    "%16, %17, %18, %19, %20, %21, %22, %23, %24, %25, %26, %27, %28, %29, %30, %31, "
    "%32, %33, %34, %35, %36, %37, %38, %39, %40, %41, %42, %43, %44, %45, %46, %47, "
    "%48, %49, %50, %51, %52, %53, %54, %55, %56, %57, %58, %59, %60, %61, %62, %63, "
    "%64, %65, %66, %67, %68, %69, %70, %71, %72, %73, %74, %75, %76, %77, %78, %79, "
    "%80, %81, %82, %83, %84, %85, %86, %87, %88, %89, %90, %91, %92, %93, %94, %95}, "
    "{%96, %97, %98, %99}, %100, p, 1, 1, 1;}"
    : "+f"(d[0]), "+f"(d[1]), "+f"(d[2]), "+f"(d[3]), "+f"(d[4]), "+f"(d[5]), "+f"(d[6]), "+f"(d[7]),
      "+f"(d[8]), "+f"(d[9]), "+f"(d[10]), "+f"(d[11]), "+f"(d[12]), "+f"(d[13]), "+f"(d[14]), "+f"(d[15]),
      "+f"(d[16]), "+f"(d[17]), "+f"(d[18]), "+f"(d[19]), "+f"(d[20]), "+f"(d[21]), "+f"(d[22]), "+f"(d[23]),
      "+f"(d[24]), "+f"(d[25]), "+f"(d[26]), "+f"(d[27]), "+f"(d[28]), "+f"(d[29]), "+f"(d[30]), "+f"(d[31]),
      "+f"(d[32]), "+f"(d[33]), "+f"(d[34]), "+f"(d[35]), "+f"(d[36]), "+f"(d[37]), "+f"(d[38]), "+f"(d[39]),
      "+f"(d[40]), "+f"(d[41]), "+f"(d[42]), "+f"(d[43]), "+f"(d[44]), "+f"(d[45]), "+f"(d[46]), "+f"(d[47]),
      "+f"(d[48]), "+f"(d[49]), "+f"(d[50]), "+f"(d[51]), "+f"(d[52]), "+f"(d[53]), "+f"(d[54]), "+f"(d[55]),
      "+f"(d[56]), "+f"(d[57]), "+f"(d[58]), "+f"(d[59]), "+f"(d[60]), "+f"(d[61]), "+f"(d[62]), "+f"(d[63]),
      "+f"(d[64]), "+f"(d[65]), "+f"(d[66]), "+f"(d[67]), "+f"(d[68]), "+f"(d[69]), "+f"(d[70]), "+f"(d[71]),
      "+f"(d[72]), "+f"(d[73]), "+f"(d[74]), "+f"(d[75]), "+f"(d[76]), "+f"(d[77]), "+f"(d[78]), "+f"(d[79]),
      "+f"(d[80]), "+f"(d[81]), "+f"(d[82]), "+f"(d[83]), "+f"(d[84]), "+f"(d[85]), "+f"(d[86]), "+f"(d[87]),
      "+f"(d[88]), "+f"(d[89]), "+f"(d[90]), "+f"(d[91]), "+f"(d[92]), "+f"(d[93]), "+f"(d[94]), "+f"(d[95])
    : "r"(a[0]), "r"(a[1]), "r"(a[2]), "r"(a[3]), "l"(db), "r"(add));
}
__device__ __forceinline__ void wgmma_n48(float (&d)[24], const uint32_t (&a)[4], uint64_t db, int add) {
  asm volatile("{.reg .pred p; setp.ne.b32 p, %29, 0; wgmma.mma_async.sync.aligned.m64n48k16.f32.bf16.bf16 "
    "{%0, %1, %2, %3, %4, %5, %6, %7, %8, %9, %10, %11, %12, %13, %14, %15, "
    "%16, %17, %18, %19, %20, %21, %22, %23}, "
    "{%24, %25, %26, %27}, %28, p, 1, 1, 1;}"
    : "+f"(d[0]), "+f"(d[1]), "+f"(d[2]), "+f"(d[3]), "+f"(d[4]), "+f"(d[5]), "+f"(d[6]), "+f"(d[7]),
      "+f"(d[8]), "+f"(d[9]), "+f"(d[10]), "+f"(d[11]), "+f"(d[12]), "+f"(d[13]), "+f"(d[14]), "+f"(d[15]),
      "+f"(d[16]), "+f"(d[17]), "+f"(d[18]), "+f"(d[19]), "+f"(d[20]), "+f"(d[21]), "+f"(d[22]), "+f"(d[23])
    : "r"(a[0]), "r"(a[1]), "r"(a[2]), "r"(a[3]), "l"(db), "r"(add));
}
__device__ __forceinline__ void wgmma_n80(float (&d)[40], const uint32_t (&a)[4], uint64_t db, int add) {
  asm volatile("{.reg .pred p; setp.ne.b32 p, %45, 0; wgmma.mma_async.sync.aligned.m64n80k16.f32.bf16.bf16 "
    "{%0, %1, %2, %3, %4, %5, %6, %7, %8, %9, %10, %11, %12, %13, %14, %15, "
    "%16, %17, %18, %19, %20, %21, %22, %23, %24, %25, %26, %27, %28, %29, %30, %31, "
    "%32, %33, %34, %35, %36, %37, %38, %39}, "
    "{%40, %41, %42, %43}, %44, p, 1, 1, 1;}"
    : "+f"(d[0]), "+f"(d[1]), "+f"(d[2]), "+f"(d[3]), "+f"(d[4]), "+f"(d[5]), "+f"(d[6]), "+f"(d[7]),
      "+f"(d[8]), "+f"(d[9]), "+f"(d[10]), "+f"(d[11]), "+f"(d[12]), "+f"(d[13]), "+f"(d[14]), "+f"(d[15]),
      "+f"(d[16]), "+f"(d[17]), "+f"(d[18]), "+f"(d[19]), "+f"(d[20]), "+f"(d[21]), "+f"(d[22]), "+f"(d[23]),
      "+f"(d[24]), "+f"(d[25]), "+f"(d[26]), "+f"(d[27]), "+f"(d[28]), "+f"(d[29]), "+f"(d[30]), "+f"(d[31]),
      "+f"(d[32]), "+f"(d[33]), "+f"(d[34]), "+f"(d[35]), "+f"(d[36]), "+f"(d[37]), "+f"(d[38]), "+f"(d[39])
    : "r"(a[0]), "r"(a[1]), "r"(a[2]), "r"(a[3]), "l"(db), "r"(add));
}

__device__ __forceinline__ constexpr int wo_off(int i) { return (i < 4 ? 8 + i : i - 4) * WO; }
__device__ __forceinline__ void load_stage(const Params& P, uint32_t sb, int st, int j, int g, int rank) {
  const uint32_t fb = sb + OFF_BAR + 8 * (B_FULL + (st & 3)), a = sb + (st & 3) * STAGE;
  mbar_expect_tx(fb, STAGE);
  tma2(a, &P.xa, fb, 640 * rank + 64 * st, 128 * j);
  tma3_both(a + STAGE_A + rank * (STAGE_B0 / 2), &P.w0, fb, 80 * g, 64 * st + 32 * rank, 0);
  tma3_both(a + STAGE_A + STAGE_B0 + rank * (STAGE_B1 / 2), &P.w1, fb, 80 * g + 64, 64 * st + 32 * rank, 0);
}

__device__ __forceinline__ void run_producer(const Params& P, uint8_t* sm, uint32_t sb, int b) {
  const int rank = b & 1, g = (b >> 1) & 7, j = b >> 4;
  const uint32_t bar = sb + OFF_BAR;
#pragma unroll 1
  for (int st = EARLY; st < 10; ++st) {
    if (st == GO_ST) bar_sync<NB_GO, 160>();
    mbar_wait(bar + 8 * (B_EMPTY + (st & 3)), (((st + 1) >> 2) + 1) & 1);
    if (elect_one()) {
      load_stage(P, sb, st, j, g, rank);
      const int i = (TOUCH_MAP >> (4 * st - 8)) & 15, k = st - LMPF_AT;
      if (!LSU_TOUCH && i < 3 && b < N_FFN) {
        asm volatile("mbarrier.expect_tx.shared::cta.b64 [%0], 2560;" ::"r"(bar + 8 * B_HALO) : "memory");
        tma3(sb + OFF_SINK, &P.tg + i, bar + 8 * B_HALO, i < 2 ? 64 * (b >> 2) : 0, i < 2 ? 0 : 16 * b, i < 2 ? 2 * rank + (g & 1) : 0);
      }
      if ((uint32_t)k < 5u) bulk_prefetch(P.wmod + (5 * b + k) * 3840 + 1280, 5120);
      if (st == 7) bulk_prefetch(P.wo + b * 3200, 6400);
    }
  }
  TSTAMP(1);
#pragma unroll 1
  for (int i = 0; i < 8; ++i) {
    if (i < 2 || i == 4 || i == 7) mbar_wait(bar + 8 * (B_EMPTY + (i < 2 ? 2 + i : i & 1)), i == 0);
    if (elect_one()) {
      const uint32_t fb = bar + 8 * (i ? B_WO1 : B_WO0), a = sb + (i < 4 ? 8 + i : i - 4) * WO;
      if (i == 0) {
        mbar_expect_tx(bar + 8 * B_XS, 25600);
        tma2(sb + OFF_LM, &P.wm, bar + 8 * B_XS, 1280 + 80 * (b & 31), 160 * (b >> 5));
      }
      if (i < 2) mbar_expect_tx(fb, i ? 7 * 12800 : 12800);
      if ((i & 1) == rank) {
        const int k0 = 80 * (i ? i - (i <= g) : g);
        tma3_both(a, &P.woa, fb, 80 * g, k0, 0);
        tma2_both(a + 10240, &P.wob, fb, 80 * g + 64, k0);
      }
    }
  }
  TSTAMP(3);
  if (b < N_FFN) {
    if (elect_one()) {
      mbar_expect_tx(bar + 8 * B_ACT, 1024);
      mbar_expect_tx(bar + 8 * B_FFN, 40960);
    }
    mbar_wait(bar + 8 * B_GO, 1);
    uint32_t next = clock32();
#pragma unroll 1
    for (int i = 0; i < 6; ++i) {
      if (i == 3) bar_sync<NB_LM, 128>();
      wait_until(next);
      next += FFN_GAP;
      if (elect_one())
        tma3(sb + OFF_FFN + 10240 * i, &P.wg + (i >> 1), bar + 8 * (i < 4 ? B_FFN : B_XS), i < 4 ? 32 * (b >> 1) : 0, i < 4 ? 0 : 16 * b, i < 4 ? 2 * rank + (i & 1) : 5 * (i & 1));
    }
  }
  TSTAMP(4);
}

__device__ __forceinline__ void run_helper(const Params& P, uint8_t* sm, uint32_t sb, int b, int hw, uint32_t ep, int budget, uint32_t poll_at) {
  const int h = threadIdx.x - 256, lane = h & 31, gq = lane >> 2, t = lane & 3, rank = b & 1, g = (b >> 1) & 7, j = b >> 4;
  const uint32_t bar = sb + OFF_BAR, prm = sb + OFF_PRM;
  uint4* const box = P.sc + b * BOX;
  const bool main20 = lane < 20;
  const int fin = 128 * (b >> 4) + 16 * ((b >> 2) & 3) + 2 * (b & 3) + (lane & 1) + 32 * (lane & 2) + 2 * (lane & 4);
  const int which = main20 ? 2 - hw : 3, fsl = (fin * 205) >> 14;
  const int q4 = main20 ? lane : hw < 2 ? min(10 * hw + lane - 20, 19) : (fin - 80 * fsl) >> 2;
  uint32_t wr[2];
  asm volatile("ld.global.nc.v2.u32 {%0, %1}, [%2];" : "=r"(wr[0]), "=r"(wr[1]) : "l"(P.wr + 80 * g + 4 * q4));
  uint32_t cw;
  asm volatile("ld.global.nc.u32 %0, [%1];" : "=r"(cw) : "l"(P.c + 160 * (b >> 5) + 2 * min(h, 79)));
  sts1(sb + OFF_SILU + 4 * min(h, 79), pack2(bf_lo(cw) * sigmoid(bf_lo(cw)), bf_hi(cw) * sigmoid(bf_hi(cw))));
  if (h < 4) sts1(prm + R_ONE + 4 * h, 0x3F803F80u);
  wait_until(poll_at);
  {
    uint32_t v[4][4];
    const int h80 = min(h, 79);
    const uint4* src = at<16>(P.sc, (h80 >> 2) * BOX + 4 * j + (h80 & 3));
#pragma unroll 1
    do {
#pragma unroll
      for (int i = 0; i < 4; ++i) ld_rlx4(v[i], src + i * 20 * BOX);
    } while (retry<~0u>(stale<4, 2>(v, ep), budget));
#pragma unroll
    for (int i = 0; i < 4; ++i) sts2(sb + OFF_C1 + 16 * h80 + 1280 * (i & 1) + (i < 2 ? 8 : 0), v[i][0], v[i][1]);
    mbar_arrive(bar + 8 * B_TAB);
  }
  TSTAMP(3);
  bar_sync<NB_GO, 160>();
  {
    const char* src = hw == 2 ? at<128>(reinterpret_cast<const char*>(P.wdown), 160 * b + lane)
                              : at<128>(reinterpret_cast<const char*>(hw ? P.wup : P.wgate), (160 * (b & 3) + lane) * 27 + (b >> 2));
    uint32_t next = clock32() + TOUCH_AT + hw * (TOUCH_GAP / 3);
#pragma unroll 1
    for (int i = 0; i < 8; ++i) {
      wait_until(next);
      next += TOUCH_GAP;
      if (i < 5 && b < N_FFN) asm volatile("cp.async.cg.shared.global.L2::128B [%0], [%1], 16;" ::"r"(sb + OFF_SINK + 16 * h), "l"(src) : "memory");
      src += hw == 2 ? 4096 : 32 * 3456;
      st_rlx4(at<16>(box + M_HALO, h + 96 * i), ~ep, ~ep, ~ep, ~ep);
    }
  }
  bar_sync<NB_HELP, 96>();
  TSTAMP(5);

  {
    float d0[4] = {0.f, 0.f, 0.f, 0.f}, d1[4] = {0.f, 0.f, 0.f, 0.f};
    uint32_t wa = sb + OFF_LM + (8 * (lane >> 4) + (lane & 7)) * 160 + 64 * hw + (lane & 8) * 2, sa = sb + OFF_SILU + (lane >> 3) * 16;
    mbar_wait(bar + 8 * B_XS, 1);
    {
      uint32_t hv[2][4] = {};
      const int q = min(2 * hw, 3);
      const uint4* const src = at<16>(box + (M_HALO - 16 * BOX), 32 * q + lane);
      mbar_wait(bar + 8 * B_EMPTY, 0);
      wait_until(clock32() + HALO_GAP);
      if (j > 0) gather<2, 32, 0>(hv, src, ep, budget);
      stsm4(sb + OFF_H + 512 * q + 16 * lane, hv[0]);
      stsm4(sb + OFF_H + 512 * q + 16 * lane + 512, hv[1]);
      bar_arrive<NB_HALO, 128>();
      if (j > 0) TSTAMP(4);
    }
    mbar_wait(bar + 8 * (B_EMPTY + 1), 0);
    TSTAMP(6);
#pragma unroll 1
    for (int u = 0; u < 5; ++u) {
      uint32_t a[4][4], s[4];
      ldsm4(s, sa);
#pragma unroll
      for (int i = 0; i < 4; ++i) ldsm4t(a[i], wa + (i >> 1) * 2560 + (i & 1) * 32);
      mma16(d0, a[0], s[0], s[1], d0);
      mma16(d1, a[1], s[0], s[1], d1);
      mma16(d0, a[2], s[2], s[3], d0);
      mma16(d1, a[3], s[2], s[3], d1);
      wa += 5120;
      sa += 64;
    }
    const float v = t & 2 ? (t & 1 ? d1[2] : d1[0]) : (t & 1 ? d0[2] : d0[0]);
    if (32 * hw + 8 * t < 80) st_rlx1(at<4>(box + M_LATE, 32 * hw + 8 * t + gq), tag(u32(v), ep));
  }
  if (b < N_FFN) {
    if (h == 0) mbar_expect_tx(bar + 8 * B_XS, 20480);
    bar_arrive<NB_LM, 128>();
  }
  TSTAMP(7);
  wait_until(clock32() + LATE_GAP);
  {
    uint32_t v[4][4];
    const uint4* src = at<16>(P.sc + M_LATE, (8 * which + (main20 || hw < 2 ? g : fsl & 7)) * BOX + q4);
#pragma unroll 1
    do {
#pragma unroll
      for (int i = 0; i < 4; ++i) ld_rlx4(v[i], src + i * 32 * BOX);
    } while (retry<1>(stale<4, 0>(v, ep) | stale<4, 1>(v, ep) | stale<4, 2>(v, ep) | stale<4, 3>(v, ep), budget));
    const uint32_t one = which == 2 ? 0x3F803F80u : 0u;
    uint32_t w[2], pw[2];
#pragma unroll
    for (int e = 0; e < 2; ++e) {
      w[e] = fma2(pack2(f32(v[0][2 * e]) + f32(v[1][2 * e]) + f32(v[2][2 * e]) + f32(v[3][2 * e]),
                        f32(v[0][2 * e + 1]) + f32(v[1][2 * e + 1]) + f32(v[2][2 * e + 1]) + f32(v[3][2 * e + 1])), 0x3F803F80u, one);
      pw[e] = fma2(w[e], wr[e], 0x80008000u);
    }
    const uint32_t dst = prm + (main20 || hw < 2 ? 160 * which + 8 * q4 : R_FIN + 4 * (lane & 6));
    sts2(dst, w[0], w[1]);
    sts2(dst + 800, pw[0], pw[1]);
    float s = main20 ? bf_lo(pw[0]) + bf_hi(pw[0]) + bf_lo(pw[1]) + bf_hi(pw[1]) : 0.f;
#pragma unroll
    for (int o = 16; o > 0; o >>= 1) s += shx(s, o);
    sts1(sb + OFF_KEY + 64 + 4 * hw, u32(s));
    mbar_arrive(bar + 8 * B_TAB);
    mbar_wait(bar + 8 * B_TAB, 1);
  }
  TSTAMP(8);

  uint32_t ckey = 0;
  uint4* const odst = reinterpret_cast<uint4*>(P.out + (256 * j + rank) * 640 + 80 * g);
  if (hw == 0) {
    const uint32_t tile = min(4 * (lane & 3) + (lane >> 3), 9) * 16;
    uint32_t c1[4], sv[4], gb[4], x[4];
    ldsm4(c1, prm + R_C1 + tile);
    ldsm4(sv, prm + R_SB + tile);
    ldsm4(gb, prm + (lane & 4 ? R_GB + tile : R_ONE));
    const uint32_t bc = lds1(sb + OFF_KEY + 68), keep = gq & 4 ? ~0u : 0u;
    uint4* const cdst = at<16>(P.sc + M_CAND, (b - rank + (lane >> 4)) * BOX + 2 * (lane & 12) + 4 * rank + (lane & 3));
    uint32_t crow;
#pragma unroll 1
    for (int pass = DRY; pass < 2; ++pass) {
      if (pass) bar_sync<NB_KEY, 288>();
      uint32_t k0, k1;
      asm volatile("ld.shared.v2.u32 {%0, %1}, [%2];" : "=r"(k0), "=r"(k1) : "r"(sb + OFF_KEY + 8 * (lane & 7)) : "memory");
      ckey = __reduce_max_sync(0xFFFFFFFFu, k0);
      crow = (~ckey >> 1) & 127;
      TSTAMP(9);
      ldsm4(x, sb + OFF_X2 + crow * 176 + tile);
      const uint32_t nw = __shfl_sync(0xFFFFFFFFu, k1, crow >> 4), rs = dup_hi(nw), nm = dup_lo(nw);
#pragma unroll
      for (int e = 0; e < 4; ++e) x[e] = fma2(gb[e], fma2(fma2(x[e], rs, nm), c1[e], sv[e]), x[e] & keep);
      st_rlx4(cdst, tag(x[0], ep + 1 - pass), x[1], gq == 2 ? ckey : x[2], gq == 2 ? bc : x[3]);
    }
    bar_arrive<NB_PUB, 288>();
    TSTAMP(10);
    bar_sync<NB_OUT + 1, 160>();
    uint32_t next = clock32() + OUT_AT;
#pragma unroll 1
    for (int u = 0; u < 8; ++u) {
      if (u == 4) {
        bar_sync<NB_OUT, 160>();
        next = clock32() + OUT2_AT;
      }
      wait_until(next);
      next += OUT_GAP;
      if (u != crow >> 4 && elect_one())
        asm volatile("cp.async.bulk.tensor.2d.global.shared::cta.bulk_group [%0, {%2, %3}], [%1];"
                     ::"l"(&P.om), "r"(sb + OFF_OUT + 2560 * u), "r"(640 * rank + 80 * g), "r"(128 * j + 16 * u) : "memory");
    }
    asm volatile("cp.async.bulk.commit_group;" ::: "memory");
    TSTAMP(11);
  } else {
    if (b >= 80 || hw == 2) return;
    bar_sync<NB_WIN, 64>();
  }
  uint32_t m[7][4], wkey = lds1(sb + OFF_KEY + 80);
  if (b >= N_FFN) {
    gather<1, 0, 0>(m, at<64>(P.sc + M_CAND + 16, (lane & 14) * (2 * BOX) + (lane & 1)), ep, budget);
    wkey = __reduce_max_sync(0xFFFFFFFFu, m[0][2]);
  }
  const uint32_t wtok = ~wkey & 2047;
  TSTAMP(12);
  if (hw == 0) {
    const uint32_t u = (~ckey >> 5) & 7, skip = ckey == wkey ? (~ckey >> 1) & 15 : 16;
#pragma unroll
    for (int i = 0; i < 5; ++i) {
      const uint32_t v = lane + 32 * i, r = (v * 205) >> 11;
      if (r != skip) *at<16>(odst, 2560 * u + v + 150 * r) = *reinterpret_cast<const uint4*>(sm + OFF_OUT + 2560 * u + 16 * v);
    }
    st_rlx1(at<4>(box + M_EPOCH, lane), ep);
    asm volatile("cp.async.bulk.wait_group.read 0;" ::: "memory");
    TSTAMP(15);
    TALIGN(1);
    return;
  } else {
    const int cn = fin - 80 * fsl;
    gather<1, 0, 0>(m, at<16>(P.sc + M_CAND, (16 * (wtok >> 8) + (lane & 8 ? 2 * (lane & 7) : 2 * fsl + 1)) * BOX + 4 * (wtok & 1) +
                                             (lane & 8 ? 16 : 8 * (cn >> 5) + ((cn >> 1) & 3))), ep, budget);
    const uint32_t bw = cn & 16 ? (cn & 8 ? m[0][3] : m[0][2]) : (cn & 8 ? m[0][1] : m[0][0]);
    const uint32_t gw = lds1(prm + R_FIN + 4 * (lane & 6) + 4 * (b & 1));
    float r = f32(m[0][3]);
#pragma unroll
    for (int o = 1; o < 8; o <<= 1) r += shx(r, o);
    r = __shfl_sync(0xFFFFFFFFu, r, 8) + f32(wkey >> 31 ? wkey & 0x7FFFF800u : ~wkey | 0x7FFu);
    const float sg = bf_round(sigmoid(bf_round(r))), gv = lane & 1 ? bf_hi(gw) : bf_lo(gw), bv = lane & 1 ? bf_hi(bw) : bf_lo(bw);
    __nv_bfloat16* const dst = at<2>(P.out, wtok * 640 + fin);
    const uint4* const src = at<16>(P.sc + M_YP, (4 * (lane >> 3) + ((b >> 2) & 3)) * BOX + 32 * j + 8 * (b & 3) + (lane & 7));
    TSTAMP(13);
    bar_sync<NB_YP, 64>();
    if (YP_GAP) wait_until(clock32() + YP_GAP);
    gather_lazy<7, 16 * BOX, 32 * BOX, 0>(m, src, ep, budget, lane >= 24);
    TSTAMP(14);
    float y[4];
#pragma unroll
    for (int e = 0; e < 4; ++e)
      y[e] = ((f32(m[0][e]) + f32(m[1][e])) + (f32(m[2][e]) + f32(m[3][e]))) + ((f32(m[4][e]) + f32(m[5][e])) + f32(m[6][e]));
    const bool u1 = lane & 2, u2 = lane & 4;
    const float e0 = (u1 ? y[1] : y[0]) + shx(u1 ? y[0] : y[1], 2), e1 = (u1 ? y[3] : y[2]) + shx(u1 ? y[2] : y[3], 2);
    float e = (u2 ? e1 : e0) + shx(u2 ? e0 : e1, 4);
    e += shx(e, 8);
    e += shx(e, 16);
    asm volatile("{.reg .pred p; setp.lt.u32 p, %2, 8; @p st.global.b16 [%0], %1;}"
                 ::"l"(dst), "h"((uint16_t)pack2(fmaf(gv, bf_round(bf_round(e) * sg), bv), 0.f)), "r"(lane) : "memory");
  }
  TSTAMP(15);
}

#define ACC(part, i, e) ((i) < 8 ? accA[32 * (part) + 4 * ((i) & 7) + (e)] : accB[8 * (part) + 4 * ((i) & 1) + (e)])
__device__ __forceinline__ constexpr int kpos(int i) { return i == 2 ? 8 : i == 7 ? 9 : i - (i > 2) - (i > 7); }

__device__ __forceinline__ void run_consumer(const Params& P, uint8_t* sm, uint32_t sb, int b, int warp, uint32_t ep, int budget) {
  const int tid = threadIdx.x, lane = tid & 31, gq = lane >> 2, t = lane & 3, p = warp >> 2, wq = warp & 3, rb = warp ^ 4;
  const int rank = b & 1, g = (b >> 1) & 7, j = b >> 4;
  const uint32_t bar = sb + OFF_BAR;
  uint4* const box = P.sc + b * BOX;
  const float z4[4] = {0.f, 0.f, 0.f, 0.f};

  uint32_t nrm[4];
  {
    uint32_t x[5][4], ones[10];
#pragma unroll
    for (int i = 0; i < 10; ++i) ones[i] = 0x3F803F80u;
    uint4* const dst = at<8>(box + M_ST1, tid >> 4);
    mbar_wait(bar + 8 * B_XS, 0);
    TSTAMP(4);
#pragma unroll
    for (int i = 0; i < 5; ++i) lds4(x[i], sb + OFF_XS + (tid >> 4) * 1280 + (lane & 15) * 16 + 256 * i);
    float s[4], qlo, qhi, mean, rstd;
    row_stats(s, qlo, qhi, x, ones, gq);
    const float q = __shfl_sync(0xFFFFFFFFu, qlo + qhi, 4 * gq + (gq >> 1));
    float v = t & 1 ? q : s[0] + s[2];
    v += shx(v, 4);
    v += shx(v, 8);
    const uint32_t nw = norm_word(v, shx(v, 1), mean, rstd);
    if ((lane & 15) == 0) st_rlx2(dst, nw, ep);
    TSTAMP(5);
    asm volatile("setmaxnreg.inc.sync.aligned.u32 224;");
  }

  float accA[96], accB[24];
#pragma unroll
  for (int i = 0; i < 96; ++i) asm volatile("" : "=f"(accA[i]));
#pragma unroll
  for (int i = 0; i < 24; ++i) asm volatile("" : "=f"(accB[i]));
  uint32_t xr[5][4];
#pragma unroll
  for (int i = 0; i < 20; ++i) asm volatile("" : "=r"(xr[i >> 2][i & 3]));
  const uint32_t turn = keep(NB_TURN + (tid >> 7)), pass = keep(NB_TURN + 1 - (tid >> 7));
  uint4* const opub = reinterpret_cast<uint4*>(__shfl_xor_sync(0xFFFFFFFFu, reinterpret_cast<uintptr_t>(at<16>(box + M_O, tid ^ 2)), 2));
  const uint4* src[7];
  const int l2 = lane ^ 2;
  const uint32_t ha = keep(sb + OFF_H + rb * 2560 + 16 * l2), lo = keep(sb + OFF_L + rb * 1280 + 16 * l2);
  const uint32_t va = keep(sb + OFF_H + 1280 + (rb + ((lane >> 3) & 1)) * 2560 + (lane >> 4) * 128 + (l2 & 7) * 16);
  const uint32_t M = keep((2 * (t ^ 2) > gq ? 0xFFFFu : 0u) | (2 * (t ^ 2) + 1 > gq ? 0xFFFF0000u : 0u)), gk = keep(g + (tid >> 9));
  {
    uint32_t la = sb + (16 * rb + (lane & 15)) * 128 + (((lane >> 4) ^ (lane & 7)) << 4), c1a = sb + OFF_C1 + 16 * t;
    const uint32_t rel = keep(map_to_cta(bar + 8 * B_EMPTY + 16, lane & 1)), y0 = keep(8 * ((5 * g >> 2) + 1) + (tid >> 9));
    const bool two = (ha & 0x1E0) == 0;
    const uint64_t dbase = make_desc(sb + STAGE_A, 4096, 1024, 1);
    uint64_t d0 = dbase;
    uint32_t raw[4][4], cw[4][4], y = 8;
    int add = 0;
    if (p == 1) turn_pass(pass);
    {
      const uint4* const src = at<8>(P.sc + M_ST1, (16 * j + 2 * rb) * 2 * BOX + 2 * gq + rank);
      mbar_wait(bar + 8 * B_FULL, 0);
#pragma unroll
      for (int k = 0; k < 4; ++k) ldsm4(raw[k], la ^ (32 * k));
      uint32_t n0[2], n1[2];
#pragma unroll 1
      do {
        ld_rlx2(n0, src);
        ld_rlx2(n1, src + BOX);
      } while (retry<~0u>(neq2(n0[1], n1[1], ep), budget));
      TSTAMP(6);
      mbar_wait(bar + 8 * B_TAB, 0);
#pragma unroll
      for (int k = 0; k < 4; ++k) lds4(cw[k], c1a + 64 * k);
      if (warp == 0) bar_arrive<NB_GO, 160>();
      nrm[0] = dup_hi(n0[0]); nrm[1] = dup_hi(n1[0]); nrm[2] = dup_lo(n0[0]); nrm[3] = dup_lo(n1[0]);
    }
    TSTAMP(7);
#pragma unroll 1
    for (;;) {
      uint32_t af[4][4];
      c1a += 256;
#pragma unroll
      for (int k = 0; k < 16; ++k) raw[k >> 2][k & 3] = fma2(raw[k >> 2][k & 3], nrm[k & 1], nrm[2 + (k & 1)]);
      wg_wait();
      if (two) mbar_arrive_cluster(rel ^ (y & 24));
#pragma unroll
      for (int k = 0; k < 16; ++k) af[k >> 2][k & 3] = fma2(raw[k >> 2][k & 3], cw[k >> 2][(k >> 1) & 1], cw[k >> 2][2 + ((k >> 1) & 1)]);
#pragma unroll
      for (int k = 0; k < 4; ++k) lds4(cw[k], c1a + 64 * k);
      wg_fence();
      turn_wait(turn);
      constexpr uint64_t D1 = (STAGE_B0 >> 4) + ((uint64_t)64 << 16) - ((uint64_t)256 << 16) + ((uint64_t)16 << 32) - ((uint64_t)64 << 32) + ((uint64_t)2 << 62);
#pragma unroll
      for (int k = 0; k < 4; ++k) {
        wgmma_n192(accA, af[k], d0 + ((k >> 1) * (STAGE_B0 / 2) + (k & 1) * 2048 >> 4), k ? 1 : add);
        if (PASS1 == 2 * k) turn_pass(pass);
        wgmma_n48(accB, af[k], d0 + (D1 + ((k >> 1) * (STAGE_B1 / 2) + (k & 1) * 512 >> 4)), k ? 1 : add);
        if (PASS1 == 2 * k + 1) turn_pass(pass);
      }
      wg_commit();
      if (__any_sync(0xFFFFFFFFu, y - y0 < 16u)) {
#pragma unroll
        for (int i = 0; i < 5; ++i) {
          const uint32_t k = 160 * g + 32 * i + 128 - 16 * y;
          if (k < 128u) ldsm4(xr[i], la ^ k);
        }
      }
      if (y == 80) break;
      const bool wrap = (uint32_t)d0 == (uint32_t)dbase + (3 * STAGE >> 4);
      la += wrap ? -3 * STAGE : STAGE;
      d0 = wrap ? dbase : d0 + (STAGE >> 4);
      add = 1;
      mbar_wait(bar + (y & 24), (y >> 5) & 1);
#pragma unroll
      for (int k = 0; k < 4; ++k) ldsm4(raw[k], la ^ (32 * k));
      y += 8;
    }
    wg_wait();
    if (two) mbar_arrive_cluster(rel - 8);
  }
  TSTAMP(8);

  uint32_t o[5][4];

  {
    uint32_t hi[20], vl[10], kl[10], kh[10], vv[20], qf[4][4], qs[4][2];
#pragma unroll
    for (int i = 0; i < 10; ++i) {
      hi[kpos(i)] = pack2(ACC(1, i, 2), ACC(1, i, 3));
      hi[10 + i] = pack2(ACC(2, i, 2), ACC(2, i, 3));
    }
#pragma unroll
    for (int q = 0; q < 5; ++q) hi[4 * q] = tag(hi[4 * q], ep);
    if (rb == 7) {
#pragma unroll
      for (int q = 0; q < 5; ++q) st_rlx4(opub + (M_HALO - M_O - 96 + 32 * q), hi + 4 * q);
    }
    if (!PACK_FIRST) sched_fence(P.zero);
    TSTAMP(29);
#pragma unroll
    for (int i = 0; i < 10; ++i) kl[kpos(i)] = pack2(ACC(1, i, 0), ACC(1, i, 1));
#pragma unroll
    for (int hd = 0; hd < 4; ++hd) {
      const int f0 = 5 * (hd >> 1) + 3 * (hd & 1), sg = 5 * (hd >> 1) + 2;
      const bool mine = (t >> 1) == (hd & 1);
#pragma unroll
      for (int e = 0; e < 4; ++e) qf[hd][e] = pack2(ACC(0, f0 + (e >> 1), 2 * (e & 1)), ACC(0, f0 + (e >> 1), 2 * (e & 1) + 1));
#pragma unroll
      for (int e = 0; e < 2; ++e) {
        if (!(hd & 1)) qs[hd + 1][e] = pack2(ACC(0, sg, 2 * e), ACC(0, sg, 2 * e + 1));
        qs[hd][e] = mine ? qs[hd | 1][e] : 0u;
      }
    }
    sched_fence(P.zero);
#pragma unroll
    for (int q = 0; q < 5; ++q) stsm4(ha + 2560 + 512 * q, hi + 4 * q);
#pragma unroll
    for (int i = 0; i < 10; ++i) vl[i] = pack2(ACC(2, i, 0), ACC(2, i, 1));
    stsm4(lo, vl);
    stsm4(lo + 512, vl + 4);
    stsm2(lo + 1024, vl + 8);
    __syncwarp();
    if (lane == 0) mbar_arrive(bar + 8 * B_HALO);
    float S0[4][4], S1[4][4], S2[4][4];
    ldsm4t(vl, lo);
    ldsm4t(vl + 4, lo + 512);
    ldsm2t(vl + 8, lo + 1024);
    if (PACK_FIRST != 2) sched_fence(P.zero);
#pragma unroll
    for (int hd = 0; hd < 4; ++hd) {
      mma16(S1[hd], qf[hd], kl[2 * hd], kl[2 * hd + 1], z4);
      mma16(S2[hd], qf[hd], hi[2 * hd], hi[2 * hd + 1], z4);
    }
#pragma unroll
    for (int hd = 0; hd < 4; ++hd) {
      mma8(S1[hd], qs[hd][0], qs[hd][1], kl[8 + (hd >> 1)], S1[hd]);
      mma8(S2[hd], qs[hd][0], qs[hd][1], hi[8 + (hd >> 1)], S2[hd]);
    }
    {
      const uint4* const lower = opub - 2 * BOX * g;
      const uint4* const upper = lower + 2 * BOX;
#pragma unroll
      for (int i = 0; i < 7; ++i) src[i] = i < gk ? lower : upper;
    }
    TSTAMP(9);
    mbar_wait(bar + 8 * B_HALO, 0);
    if (rb == 0) bar_sync<NB_HALO, HALO3 ? 128 : 64>();
    TSTAMP(10);
    ldsm4(kh, ha);
    ldsm4(kh + 4, ha + 512);
    ldsm2(kh + 8, ha + 1024);
#pragma unroll
    for (int i = 0; i < 5; ++i) ldsm4t(vv + 4 * i, va + 256 * i);
    const float SC = 0.22360679774997896f * 1.4426950408889634f, ev = (j | rb) == 0 ? -1e9f / 0.22360679774997896f : 0.f;
    const float e4[4] = {ev, ev, ev, ev};
#pragma unroll
    for (int hd = 0; hd < 4; ++hd) mma16(S0[hd], qf[hd], kh[2 * hd], kh[2 * hd + 1], e4);
#pragma unroll
    for (int hd = 0; hd < 4; ++hd) mma8(S0[hd], qs[hd][0], qs[hd][1], kh[8 + (hd >> 1)], S0[hd]);
    const bool up0 = M == ~0u, up1 = M != 0;
    uint32_t pp[4][2];
    {
      float a[8][2], mx[8];
#pragma unroll
      for (int hd = 0; hd < 4; ++hd) {
        a[2 * hd][0] = up0 ? S0[hd][0] : S1[hd][0];
        a[2 * hd][1] = up1 ? S0[hd][1] : S1[hd][1];
        a[2 * hd + 1][0] = up0 ? S1[hd][2] : S2[hd][2];
        a[2 * hd + 1][1] = up1 ? S1[hd][3] : S2[hd][3];
      }
#pragma unroll
      for (int i = 0; i < 8; ++i) mx[i] = fmaxf(a[i][0], a[i][1]);
#pragma unroll
      for (int s = 1; s < 4; s <<= 1) {
#pragma unroll
        for (int i = 0; i < 8; ++i) mx[i] = fmaxf(mx[i], shx(mx[i], s));
      }
#pragma unroll
      for (int i = 0; i < 8; ++i) {
        const float ms = mx[i] * -SC;
        pp[i >> 1][i & 1] = pack2(ex2(fmaf(a[i][0], SC, ms)), ex2(fmaf(a[i][1], SC, ms)));
      }
    }
    float L[4][4], O[4][3][4];
#pragma unroll
    for (int hd = 0; hd < 4; ++hd) mma8(L[hd], pp[hd][0], pp[hd][1], 0x3F803F80u, z4);
#pragma unroll
    for (int hd = 0; hd < 4; ++hd) {
      const uint32_t p0 = pp[hd][0] & M, p2 = pp[hd][0] & ~M, p3 = pp[hd][1] & M, p5 = pp[hd][1] & ~M;
      const uint32_t z0 = pp[hd][0] & P.zero, z1 = pp[hd][1] & P.zero;
#pragma unroll
      for (int e = 0; e < 3; ++e) {
        const int f = 5 * (hd >> 1) + 2 * (hd & 1) + e;
        mma16(O[hd][e], p0, z0, z1, p5, vv[2 * f], vv[2 * f + 1], z4);
      }
#pragma unroll
      for (int e = 0; e < 3; ++e) mma8(O[hd][e], p2, p3, vl[5 * (hd >> 1) + 2 * (hd & 1) + e], O[hd][e]);
    }
    const bool odd = t >> 1;
#pragma unroll
    for (int hp = 0; hp < 2; ++hp) {
      const float (&A)[3][4] = O[2 * hp];
      const float (&B)[3][4] = O[2 * hp + 1];
#pragma unroll
      for (int e = 0; e < 2; ++e) {
        const float ra = rcp(L[2 * hp][2 * e]), rc = rcp(L[2 * hp + 1][2 * e]), rm = odd ? rc : ra;
        uint32_t* const d = &o[0][0] + 10 * hp + e;
        d[0] = pack2(A[0][2 * e] * ra, A[0][2 * e + 1] * ra);
        d[2] = pack2(A[1][2 * e] * ra, A[1][2 * e + 1] * ra);
        d[4] = pack2((odd ? B[0][2 * e] : A[2][2 * e]) * rm, (odd ? B[0][2 * e + 1] : A[2][2 * e + 1]) * rm);
        d[6] = pack2(B[1][2 * e] * rc, B[1][2 * e + 1] * rc);
        d[8] = pack2(B[2][2 * e] * rc, B[2][2 * e + 1] * rc);
      }
      if (hp == 0) {
#pragma unroll
        for (int s = 0; s < 2; ++s) {
          o[s][0] = tag(o[s][0], ep);
          st_rlx4(opub + 256 * s, o[s]);
        }
        if (PUB_FENCE) sched_fence(P.zero);
        if (p == 1) bar_arrive<NB_PV, 256>();
      }
    }
#pragma unroll
    for (int s = 2; s < 5; ++s) o[s][0] = tag(o[s][0], ep);
  }
  TSTAMP(11);

  float acc[40];
#pragma unroll
  for (int i = 0; i < 40; ++i) asm volatile("" : "=f"(acc[i]));
  uint32_t ga[10], pb[10], uw, nw;
  uint4* const sdst = at<16>(box + M_ST2, 16 * rb + gq);
  const uint32_t prow = sb + OFF_PRM + (lane >> 3) * 16;
  {
    const uint64_t dw = make_desc(sb, 5120, 512, 2);
    uint32_t in[NSET][7][4];
    st_rlx4(opub + 256 * 2, o[2]);
    mbar_wait(bar + 8 * B_WO0, 0);
    if (p == 0) bar_sync<NB_PV, 256>();
#pragma unroll
    for (int i = 0; i < 7; ++i) ld_rlx4(in[0][i], src[i] + 2 * BOX * i);
    wg_fence();
    turn_wait(turn);
#pragma unroll
    for (int s = 0; s < 5; ++s) {
      wgmma_n80(acc, o[s], dw + (wo_off(0) + 1024 * s >> 4), s);
      if (s == PASS0 && (PASS_AT || p == 0)) turn_pass(pass);
    }
    wg_commit();
    TSTAMP(12);
#pragma unroll
    for (int s = 0; s < 5; ++s) {
      uint32_t (&cur)[7][4] = in[s % NSET];
      if (s == 0) mbar_wait(bar + 8 * B_WO1, 0);
      else if (NSET == 2) wg_wait();
      if (s || B0) sched_fence(P.zero);
      if ((s == 0 && !B0) || retry<1>(stale<7, 0>(cur, ep), budget)) {
#pragma unroll 1
        do {
#pragma unroll
          for (int i = 0; i < 7; ++i) ld_rlx4(cur[i], src[i] + (2 * BOX * i + 256 * s));
        } while (retry<1>(stale<7, 0>(cur, ep), budget));
      }
      TSTAMP(13 + s);
      if (s < 4) {
        if (s > 1 && NSET == 3) asm volatile("wgmma.wait_group.sync.aligned 1;" ::: "memory");
#pragma unroll
        for (int i = 0; i < 7; ++i) ld_rlx4(in[(s + 1) % NSET][i], src[i] + (2 * BOX * i + 256 * (s + 1)));
      }
      if (s == 0) { st_rlx4(opub + 256 * 3, o[3]); st_rlx4(opub + 256 * 4, o[4]); }
      if (s == FGO_STEP && tid == 128) mbar_arrive(bar + 8 * B_GO);
      wg_fence();
      if (PASS_AT) turn_wait(turn);
#pragma unroll
      for (int i = 0; i < 7; ++i) {
        wgmma_n80(acc, cur[i], dw + (wo_off(i + 1) + 1024 * s >> 4), 1);
        if (i == PASS_AT - 1 && (s < 4 || p == 0)) turn_pass(pass);
      }
      wg_commit();
    }
    mbar_wait(bar + 8 * B_TAB, 1);
    ld_row(ga, prow + R_GA);
    ldsm4(pb, lane & 1 ? prow + R_P : sb + OFF_PRM + R_ONE);
    ldsm4(pb + 4, lane & 1 ? prow + R_P + 64 : sb + OFF_PRM + R_ONE);
    ldsm2(pb + 8, lane & 1 ? prow + R_P + 128 : sb + OFF_PRM + R_ONE);
    uw = tag(lds1(sb + OFF_KEY + 64), ep);

    wg_wait();
  }
  TSTAMP(18);

  uint32_t wf[20][4];
#pragma unroll
  for (int i = 0; i < 80; ++i) asm volatile("" : "=r"(wf[i >> 2][i & 3]));
  const auto load_gate = [&]() {
    mbar_wait(bar + 8 * B_FFN, 1);
#pragma unroll
    for (int i = 0; i < 20; ++i)
      ldsm4t(wf[i], sb + OFF_FFN + (lane & 8) * 2560 + (80 * wq + 8 * (lane >> 4) + (lane & 7)) * 64 + (((i & 3) ^ ((lane >> 1) & 3)) << 4) + 1024 * (i >> 2));
    TSTAMP(23);
  };
  const uint32_t trow = 16 * rb + (lane & 15), xt = sb + (lane >> 4) * 16;
  {
#pragma unroll
    for (int k = 0; k < 20; ++k) xr[k >> 2][k & 3] = fma2(ga[k >> 1], pack2(acc[2 * k], acc[2 * k + 1]), xr[k >> 2][k & 3]);
    if (WF_EARLY == 2 && p == 0 && b < N_FFN) load_gate();
    float s[4], qlo, qhi;
    row_stats(s, qlo, qhi, xr, pb, gq);
    if (t == gq >> 1) {
      st_rlx4(sdst, u32(s[0]), u32(s[1]), u32(qlo), uw);
      st_rlx4(sdst + 8, u32(s[2]), u32(s[3]), u32(qhi), uw);
    }
    sched_fence(P.zero);
    TSTAMP(19);
#pragma unroll
    for (int s5 = 0; s5 < 5; ++s5) stsm4(xt + trow * 176 + (OFF_X2 + 32 * s5), xr[s5]);
    if (WF_EARLY == 1 && p == 0 && b < N_FFN) load_gate();
    uint32_t c1[10], sv[10], gb[10], m[4][4];
    ld_row(c1, prow + R_C1);
    ld_row(sv, prow + R_SB);
    ld_row(gb, prow + R_GB);
    if (ST2_GAP) wait_until(clock32() + ST2_GAP);
    gather_lazy<4, 2 * BOX, 4 * BOX, 3>(m, at<16>(P.sc + M_ST2, (16 * j + rank + 8 * (lane & 1)) * BOX + 16 * rb + (lane >> 1)), ep, budget);
    TSTAMP(20);
#pragma unroll
    for (int e = 0; e < 4; ++e) {
      s[e] = (f32(m[0][e]) + f32(m[1][e])) + (f32(m[2][e]) + f32(m[3][e]));
      s[e] += shx(s[e], 1);
    }
    float mean, rstd;
    nw = norm_word(s[0], s[2], mean, rstd);
    const uint32_t u = u32(rstd * fmaf(-mean, s[3], s[1]));
    const uint32_t key = ((u ^ ((uint32_t)((int)u >> 31) | 0x80000000u)) | 2047u) ^ (256 * j + 32 * rb + (lane & 30) + rank);
    if (key == __reduce_max_sync(0xFFFFFFFFu, key)) sts2(sb + OFF_KEY + 8 * rb, key, nw);
    bar_arrive<NB_KEY, 288>();
    TSTAMP(21);
    const uint32_t n0 = __shfl_sync(0xFFFFFFFFu, nw, 2 * gq), n1 = __shfl_sync(0xFFFFFFFFu, nw, 2 * gq + 16);
    nrm[0] = dup_hi(n0); nrm[1] = dup_hi(n1); nrm[2] = dup_lo(n0); nrm[3] = dup_lo(n1);
#pragma unroll
    for (int k = 0; k < 20; ++k) {
      uint32_t& x = xr[k >> 2][k & 3];
      x = fma2(gb[k >> 1], fma2(fma2(x, nrm[k & 1], nrm[2 + (k & 1)]), c1[k >> 1], sv[k >> 1]), x);
    }
    bar_sync<NB_PUB, 288>();
  }
  TSTAMP(22);

  if (p == 0 && b < N_FFN) {
    if (!WF_EARLY) load_gate();
    uint32_t m[6][4];
    const uint4* src = at<16>(P.sc + M_CAND, (8 * (gq & 6) + 8 * rank + 2 * wq) * BOX + (lane & 7));
    const uint32_t far = sb + OFF_ACT + (4 * rank + wq) * 128 + gq * 16;
#pragma unroll
    for (int i = 0; i < 24; ++i) asm volatile("" : "=r"(m[i >> 2][i & 3]));
#pragma unroll 1
    for (int pass = DRY; pass < 2; ++pass) {
      if (CAND_GAP) wait_until(clock32() + CAND_GAP);
      if (pass) gather_lazy<6, 64 * BOX, 8, 0>(m, src, ep, budget);
      TSTAMP(24);
      const bool second = m[5][2] > m[4][2];
      const uint32_t wtok = ~__reduce_max_sync(0xFFFFFFFFu, max(m[4][2], m[5][2]));
      float f[4][4];
#pragma unroll
      for (int s = 0; s < 5; ++s) {
        const uint32_t b0 = second ? m[(s & 6) + 1][2 * (s & 1)] : m[s & 6][2 * (s & 1)], b1 = second ? m[(s & 6) + 1][2 * (s & 1) + 1] : m[s & 6][2 * (s & 1) + 1];
#pragma unroll
        for (int mt = 0; mt < 4; ++mt) mma16(f[mt], wf[4 * s + mt], b0, b1, s ? f[mt] : z4);
      }
      const bool e = wtok & 1;
#pragma unroll
      for (int r = 0; r < 2; ++r)
        asm volatile("{.reg .pred p; setp.eq.u32 p, %6, %7;\n"
                     "@p st.async.weak.shared::cluster.mbarrier::complete_tx::bytes.v4.f32 [%0], {%1, %2, %3, %4}, [%5];}"
                     ::"r"(map_to_cta(far, r)), "f"(e ? f[2 * r][1] : f[2 * r][0]), "f"(e ? f[2 * r][3] : f[2 * r][2]),
                       "f"(e ? f[2 * r + 1][1] : f[2 * r + 1][0]), "f"(e ? f[2 * r + 1][3] : f[2 * r + 1][2]), "r"(map_to_cta(bar + 8 * B_ACT, r)),
                       "r"(t + 4 - 4 * pass), "r"((wtok >> 8) & 3) : "memory");
      if (warp == 0) {
        sts1(sb + OFF_KEY + 80, ~wtok);
        if (b < 80) bar_arrive<NB_WIN, 64>();
      }
    }
    TSTAMP(25);
  }
#pragma unroll
  for (int s5 = 0; s5 < 5; ++s5) stsm4(xt + trow * 160 + (OFF_OUT + 32 * s5), xr[s5]);
  asm volatile("fence.proxy.async.shared::cta;" ::: "memory");
  asm volatile("bar.arrive %0, 160;" ::"r"(turn + (NB_OUT - NB_TURN)) : "memory");
  if (p == 1 && b < N_FFN) {
    const uint32_t kr = ((lane & 7) >> 1) + 4 * (lane >> 4) + 8 * (lane & 1);
    mbar_wait(bar + 8 * B_XS, 0);
#pragma unroll
    for (int i = 0; i < 10; ++i) ldsm4t(wf[i], sb + OFF_FFN + 40960 + kr * 128 + (((2 * wq + ((lane >> 3) & 1)) ^ (kr & 7)) << 4) + 2048 * i);
    TSTAMP(23);
    uint4* const ydst = at<16>(P.sc + M_YP, ((b & ~3) + wq) * BOX + 4 * (gq & 6) + 2 * (b & 3) + (gq & 1));
#pragma unroll 1
    for (int pass = DRY; pass < 2; ++pass) {
      if (pass) mbar_wait(bar + 8 * B_ACT, 1);
      TSTAMP(24);
      float v[8];
#pragma unroll
      for (int i = 0; i < 8; ++i) v[i] = f32(lds1(sb + OFF_ACT + 128 * i + 4 * lane));
      const float gu = bf_round(((v[0] + v[1]) + (v[2] + v[3])) + ((v[4] + v[5]) + (v[6] + v[7])));
      const float a = bf_round(gu * sigmoid(gu)) * shx(gu, 1);
      const uint32_t aw = pack2(a, shx(a, 2));
      const uint32_t b0 = __shfl_sync(0xFFFFFFFFu, aw, 4 * t), b1 = __shfl_sync(0xFFFFFFFFu, aw, 4 * t + 16);
      const bool odd = gq & 1;
      float y[5][4];
#pragma unroll
      for (int q = 0; q < 5; ++q) mma16(y[q], wf[2 * q], odd ? 0u : b0, odd ? 0u : b1, z4);
#pragma unroll
      for (int q = 0; q < 5; ++q) {
        mma16(y[q], wf[2 * q + 1], odd ? b0 : 0u, odd ? b1 : 0u, y[q]);
        asm volatile("{.reg .pred p; .reg .b128 q; setp.eq.u32 p, %5, 0; mov.b128 q, {%1, %2, %3, %4}; @p st.relaxed.gpu.global.b128 [%0], q;}"
                     ::"l"(ydst + 32 * q), "r"(tag(u32(y[q][0]), ep)), "r"(u32(y[q][1])), "r"(u32(y[q][2])), "r"(u32(y[q][3])), "r"(t + 1 - pass) : "memory");
      }
    }
    if (warp == 4 && b < 80) bar_arrive<NB_YP, 64>();
    TSTAMP(25);
  }
}

__global__ void __cluster_dims__(2, 1, 1) __launch_bounds__(384, 1) fused_block_kernel(const __grid_constant__ Params P) {
  extern __shared__ __align__(1024) uint8_t sm[];
  const uint32_t sb = (uint32_t)__cvta_generic_to_shared(sm), t0 = clock32();
  const int tid = threadIdx.x, lane = tid & 31;
  uint32_t key = blockIdx.x;
  asm("mov.u32 %0, %%smid;" : "=r"(key));
  const int c = key >> 1, rank = blockIdx.x & 1, u = (c & 48) + 2 * (c & 7) + ((c >> 3) & 1) - (c & 32 ? c & 7 : 0), kb = 2 * u + rank;
  uint32_t cv = 0;
  {
    const __nv_bfloat16* src = at<16>(P.wmod, (320 * rank + (tid >> 2)) * 480 + 4 * u + (tid & 3));
    const uint32_t dst = sb + 3 * STAGE + 16 * (tid ^ ((tid >> 3) & 3));
    if (tid < (c < 40 ? 320 : 0)) {
#pragma unroll
      for (int i = 0; i < 4; ++i)
        asm volatile("cp.async.cg.shared.global.L2::128B [%0], [%1], 16;" ::"r"(dst + 5120 * i), "l"(src + i * 80 * 3840) : "memory");
      asm volatile("ld.relaxed.gpu.global.u16 %0, [%1];" : "=r"(cv) : "l"(at<2>(P.c, 320 * rank + 10 * (tid & 24) + ((tid >> 2) & ~7) + (tid & 7))) : "memory");
    }
  }
  TSTAMP(26);
  const int warp = __shfl_sync(0xFFFFFFFFu, tid >> 5, 0);
  const bool gemv = warp < 10 && c < 40;
  const uint32_t bar = sb + OFF_BAR;
  if (warp >= 10 && elect_one()) {
    const uint32_t a = bar + 32 * (11 - warp);
    mbar_init(bar + 8 * warp, 1);
#pragma unroll
    for (int i = 0; i < 4; ++i) mbar_init(a + 8 * i, warp == 10 ? 16 : 1);
    mbar_init(bar + 8 * (warp - 2), warp == 10 ? 8 : 96);
    asm volatile("fence.mbarrier_init.release.cluster;" ::: "memory");
    asm volatile("prefetch.tensormap [%0];" ::"l"(&P.xa) : "memory");
    asm volatile("prefetch.tensormap [%0];" ::"l"(&P.w0 + (warp - 10)) : "memory");
  }
  __syncwarp();
  asm volatile("barrier.cluster.arrive.relaxed.aligned;" ::: "memory");
  const int q7 = ((c - 32) * 37) >> 8, pa = 8 * (c & 7) + (c >> 3), pb = 8 * c - 55 * q7 - 244, pr = pick(c < 32, pa, pick(c < 60, pb, c - 58)), b = 2 * pr + rank;
  if (BY_SM && (c >> 1) == 30) {
    wait_until(t0 + 4000);
    return;
  }
  uint4* const box = P.sc + b * BOX;
  int budget = SPIN_LIMIT;
  uint32_t e0 = 0;
  TSTAMP(27);
  if (warp == 11) {
    asm volatile("barrier.cluster.wait.aligned;" ::: "memory");
    TSTAMP(28);
#pragma unroll 1
    for (int st = 0; st < EARLY; ++st) {
      wait_until(t0 + S0_AT + st * S_GAP);
      if (elect_one()) load_stage(P, sb, st, b >> 4, pr & 7, rank);
    }
  } else {
    if (warp != 10) e0 = ld_rlx1(at<4>(box + M_EPOCH, lane));
    if (warp == 10) {
      uint4* const dst = at<16>(P.sc, kb * BOX + lane);
      if (c < 40) st_rlx4(dst, 0u, 0u, 0u, 0u);
      st_rlx1(at<4>(box + M_ST1, lane), 0u);
      asm volatile("barrier.cluster.wait.aligned;" ::: "memory");
      wait_until(t0 + (b & 8 ? XS_HI : XS_AT));
      if (elect_one()) {
        mbar_expect_tx(bar + 8 * B_GO, c < 40 ? 1280 : 0);
        mbar_expect_tx(bar + 8 * B_XS, 20480);
        bulk_load(sb + OFF_XS, P.x + b * 10240, 20480, bar + 8 * B_XS);
      }
      TSTAMP(28);
      e0 = ld_rlx1(at<4>(box + M_EPOCH, lane));
      TALIGN(0);
      if (c < 40) {
        const uint32_t ep = next_epoch(e0);
        mbar_wait(bar + 8 * B_GO, 0);
        TSTAMP(1);
        float v[10];
#pragma unroll
        for (int i = 0; i < 10; ++i) v[i] = f32(lds1(sb + OFF_RED + 128 * i + 4 * lane));
        float s = ((v[0] + v[1]) + (v[2] + v[3])) + ((v[4] + v[5]) + (v[6] + v[7])) + (v[8] + v[9]);
        s += shx(s, 16);
        const uint32_t w = fma2(pack2(s, shx(s, 1)), 0x3F803F80u, kb < 40 ? 0u : 0x3F803F80u);
        st_rlx4(dst, __shfl_sync(0xFFFFFFFFu, w, 2 * (lane & 3)), __shfl_sync(0xFFFFFFFFu, w, 2 * (lane & 3) + 8), ep, ep);
        TSTAMP(2);
      }
    } else if (gemv) {
      const float x = bf_lo(cv), s = x * sigmoid(x);
      const uint32_t sw = pack2(s, shx(s, 1));
      uint32_t bw[4], a[4][4];
#pragma unroll
      for (int i = 0; i < 4; ++i) bw[i] = __shfl_sync(0xFFFFFFFFu, sw, 8 * i + 2 * (lane & 3));
      const uint32_t far = map_to_cta(sb, (lane >> 1) & 1), dst = far + OFF_RED + 128 * warp + 64 * rank + 32 * (lane & 1) + (lane & 28);
      const uint32_t la = sb + 3 * STAGE + 512 * warp + (lane >> 4) * 5120 + (lane & 7) * 64 + ((((lane >> 3) & 1) ^ ((lane >> 1) & 3)) << 4);
      asm volatile("barrier.cluster.wait.aligned;" ::: "memory");
      sched_fence(P.zero);
      asm volatile("cp.async.wait_all;" ::: "memory");
      __syncwarp();
      TSTAMP(28);
#pragma unroll
      for (int i = 0; i < 4; ++i) ldsm4t(a[i], (la ^ (32 * (i & 1))) + (i >> 1) * 10240);
      float d[2][4];
      const float z4[4] = {0.f, 0.f, 0.f, 0.f};
#pragma unroll
      for (int i = 0; i < 4; ++i) mma16(d[i & 1], a[i], bw[i & 2], bw[(i & 2) + 1], i < 2 ? z4 : d[i & 1]);
      const float v = lane & 2 ? (lane & 1 ? d[1][2] : d[1][0]) : (lane & 1 ? d[0][2] : d[0][0]);
      asm volatile("st.async.weak.shared::cluster.mbarrier::complete_tx::bytes.f32 [%0], %1, [%2];" ::"r"(dst), "f"(v), "r"(far + OFF_BAR + 8 * B_GO) : "memory");
      TSTAMP(1);
    } else {
      asm volatile("barrier.cluster.wait.aligned;" ::: "memory");
    }
  }
  if (warp >= 8) {
    asm volatile("setmaxnreg.dec.sync.aligned.u32 56;");
    if (warp == 11) {
      wait_until(t0 + WPF0_AT);
      if (elect_one()) bulk_prefetch(P.wqkv + (128 + b) * 1920, 3840);
      wait_until(t0 + WPF_AT);
      if (elect_one()) bulk_prefetch(P.wqkv + (256 + 3 * b) * 1920, 11520);
      wait_until(t0 + S2_AT);
      run_producer(P, sm, sb, b);
    } else {
      run_helper(P, sm, sb, b, warp - 8, next_epoch(e0), budget, t0 + POLL_AT);
    }
    TDUMP();
  } else {
    run_consumer(P, sm, sb, b, warp, next_epoch(e0), budget);
    TDUMP();
  }
}

typedef CUresult (*EncodeFn)(CUtensorMap*, CUtensorMapDataType, cuuint32_t, void*, const cuuint64_t*, const cuuint64_t*, const cuuint32_t*,
                             const cuuint32_t*, CUtensorMapInterleave, CUtensorMapSwizzle, CUtensorMapL2promotion, CUtensorMapFloatOOBfill);

void encode(EncodeFn fn, CUtensorMap* m, const void* base, int rank, const cuuint64_t* dims, const cuuint64_t* strides, const cuuint32_t* box,
            CUtensorMapSwizzle sw) {
  const cuuint32_t es[3] = {1, 1, 1};
  fn(m, CU_TENSOR_MAP_DATA_TYPE_BFLOAT16, rank, const_cast<void*>(base), dims, strides, box, es, CU_TENSOR_MAP_INTERLEAVE_NONE, sw,
     CU_TENSOR_MAP_L2_PROMOTION_L2_128B, CU_TENSOR_MAP_FLOAT_OOB_FILL_NONE);
}

}

extern "C" void kernel_launch(void* const* d_in, const int* in_sizes, int n_in, void* d_out, int out_size) {
  (void)in_sizes; (void)n_in; (void)out_size;
  static EncodeFn fn = nullptr;
  static void* scratch = nullptr;
  if (!fn) {
    void* f = nullptr;
    cudaDriverEntryPointQueryResult q;
    cudaGetDriverEntryPoint("cuTensorMapEncodeTiled", &f, cudaEnableDefault, &q);
    fn = (EncodeFn)f;
    cudaFuncSetAttribute(fused_block_kernel, cudaFuncAttributeMaxDynamicSharedMemorySize, SMEM_BYTES);
    cudaGetSymbolAddress(&scratch, g_scratch);
  }
  Params P;
  P.sc = (uint4*)scratch;
  P.zero = 0;
  const cuuint64_t xd[2] = {1280, 1024}, xs[1] = {2560};
  const cuuint32_t xb[2] = {64, 128};
  encode(fn, &P.xa, d_in[0], 2, xd, xs, xb, CU_TENSOR_MAP_SWIZZLE_128B);
  const cuuint32_t ob[2] = {80, 16};
  encode(fn, &P.om, d_out, 2, xd, xs, ob, CU_TENSOR_MAP_SWIZZLE_NONE);
  const cuuint64_t wd3[3] = {640, 640, 3}, ws3[2] = {3840, 1280};
  const cuuint32_t w0b[3] = {64, 32, 3}, w1b[3] = {16, 32, 3};
  encode(fn, &P.w0, d_in[1], 3, wd3, ws3, w0b, CU_TENSOR_MAP_SWIZZLE_128B);
  encode(fn, &P.w1, d_in[1], 3, wd3, ws3, w1b, CU_TENSOR_MAP_SWIZZLE_32B);
  const cuuint64_t md[2] = {3840, 640}, ms[1] = {7680};
  const cuuint32_t mb[2] = {80, 160};
  encode(fn, &P.wm, d_in[9], 2, md, ms, mb, CU_TENSOR_MAP_SWIZZLE_NONE);
  const cuuint64_t od3[3] = {608, 640, 2}, os3[2] = {1280, 64}, od2[2] = {640, 640}, os2[1] = {1280};
  const cuuint32_t oab[3] = {32, 80, 2}, obb[2] = {16, 80};
  encode(fn, &P.woa, d_in[2], 3, od3, os3, oab, CU_TENSOR_MAP_SWIZZLE_64B);
  encode(fn, &P.wob, d_in[2], 2, od2, os2, obb, CU_TENSOR_MAP_SWIZZLE_64B);
  const cuuint64_t gd[3] = {1728, 160, 4}, gs[2] = {3456, 160 * 3456}, dd[3] = {64, 1728, 10}, ds[2] = {1280, 128};
  const cuuint32_t gb[3] = {32, 160, 1}, db[3] = {64, 16, 5}, tgb[3] = {8, 160, 1}, tdb[3] = {8, 16, 10};
  encode(fn, &P.wg, d_in[5], 3, gd, gs, gb, CU_TENSOR_MAP_SWIZZLE_64B);
  encode(fn, &P.wu, d_in[6], 3, gd, gs, gb, CU_TENSOR_MAP_SWIZZLE_64B);
  encode(fn, &P.wd, d_in[7], 3, dd, ds, db, CU_TENSOR_MAP_SWIZZLE_128B);
  encode(fn, &P.tg, d_in[5], 3, gd, gs, tgb, CU_TENSOR_MAP_SWIZZLE_NONE);
  encode(fn, &P.tu, d_in[6], 3, gd, gs, tgb, CU_TENSOR_MAP_SWIZZLE_NONE);
  encode(fn, &P.td, d_in[7], 3, dd, ds, tdb, CU_TENSOR_MAP_SWIZZLE_NONE);
  P.x = (const __nv_bfloat16*)d_in[0];
  P.wqkv = (const __nv_bfloat16*)d_in[1];
  P.wr = (const __nv_bfloat16*)d_in[4];
  P.wo = (const __nv_bfloat16*)d_in[2];
  P.wgate = (const __nv_bfloat16*)d_in[5];
  P.wup = (const __nv_bfloat16*)d_in[6];
  P.wdown = (const __nv_bfloat16*)d_in[7];
  P.c = (const __nv_bfloat16*)d_in[8];
  P.wmod = (const __nv_bfloat16*)d_in[9];
  P.out = (__nv_bfloat16*)d_out;
  fused_block_kernel<<<BY_SM ? 132 : 128, 384, SMEM_BYTES>>>(P);
}
```

```cpp
#include <cuda_runtime.h>
#include <cuda.h>
#include <cuda_bf16.h>
#include <stdint.h>

namespace {

constexpr int STAGE_A = 16384, STAGE_B0 = 24576, STAGE_B1 = 6144, STAGE = STAGE_A + STAGE_B0 + STAGE_B1;
constexpr int WO = 15360;
constexpr int OFF_FFN = 4 * WO, OFF_LM = 2 * STAGE, OFF_X2 = 4 * STAGE, OFF_OUT = 0;
constexpr int OFF_H = 4 * STAGE, OFF_L = OFF_H + 9 * 2560, OFF_XS = OFF_H, OFF_RED = OFF_L, OFF_SINK = OFF_L + 10240;
constexpr int OFF_C1 = 225280, OFF_ACT = OFF_C1, OFF_PRM = OFF_C1 + 2560, OFF_SILU = OFF_PRM + 1600;
constexpr int OFF_KEY = OFF_SILU + 320, OFF_BAR = OFF_KEY + 128, OFF_TIME = OFF_BAR + 256, SMEM_BYTES = OFF_TIME + 1536;
static_assert(OFF_H % 512 == 0, "lane bits of the halo address");
static_assert(SMEM_BYTES <= 232448 && OFF_BAR % 64 == 0, "smem");
enum { R_GA = 0, R_SB = 160, R_C1 = 320, R_GB = 480, R_FIN = 640, R_P = 800 + R_C1, R_ONE = 704 };

enum { B_FULL = 0, B_EMPTY = 4, B_HALO = 8, B_TAB = 9, B_GO = 10, B_XS = 11, B_ACT = B_FULL, B_FFN = B_FULL + 1, B_WO0 = B_FULL + 2, B_WO1 = B_FULL + 3 };
enum { NB_PV = 1, NB_TURN = 2, NB_KEY = 4, NB_HELP = 6, NB_HALO = 7, NB_PUB = 8, NB_GO = 9, NB_LM = 10, NB_OUT = 11, NB_WIN = 13, NB_YP = 14 };

enum { M_EARLY = 0, M_ST1 = 32, M_EPOCH = 40, M_HALO = 48, M_ST2 = 208, M_CAND = 336, M_LATE = 368, M_YP = 400, M_O = 560, BOX = 1840 };
__device__ uint4 g_scratch[128 * BOX];

constexpr int N_FFN = 108;
#define BY_SM 1
#define NAP 20
#define XS_AT 600
#define S_GAP 2200
#define POLL_AT 4000
#define WPF_AT 4500
#define LMPF_AT 4
#define TOUCH_AT 1000
#define TOUCH_GAP 1100
#define HALO_GAP 400
#define LATE_GAP 2000
#define FGO_STEP 3
#define FFN_GAP 300
#define ST2_GAP 40
#define OUT_AT 400
#define OUT_GAP 80
#define YP_GAP 300
#define PASS1 5
#define PASS0 2
#define PASS_AT 3
constexpr int SPIN_LIMIT = 1 << 16;

struct Params {
  const __nv_bfloat16 *wmod, *c, *x;
  uint4* sc;
  uint32_t zero;
  const __nv_bfloat16 *wqkv, *wr, *wo, *wgate, *wup, *wdown;
  __nv_bfloat16* out;
  CUtensorMap xa, w0, w1, wm, woa, wob, wg, wu, wd, om;
};

__device__ __forceinline__ uint32_t clock32() {
  uint32_t c;
  asm volatile("mov.u32 %0, %%clock;" : "=r"(c));
  return c;
}
#define TSTAMP(i) do { } while (0)
#define TDUMP() do { } while (0)
#define TALIGN(k) do { } while (0)

__device__ __forceinline__ void mbar_init(uint32_t b, uint32_t c) { asm volatile("mbarrier.init.shared::cta.b64 [%0], %1;" ::"r"(b), "r"(c) : "memory"); }
__device__ __forceinline__ void mbar_expect_tx(uint32_t b, uint32_t n) { asm volatile("mbarrier.arrive.expect_tx.shared::cta.b64 _, [%0], %1;" ::"r"(b), "r"(n) : "memory"); }
__device__ __forceinline__ void mbar_arrive(uint32_t b) { asm volatile("mbarrier.arrive.shared::cta.b64 _, [%0];" ::"r"(b) : "memory"); }
__device__ __forceinline__ uint32_t map_to_cta(uint32_t a, uint32_t rank) {
  uint32_t r;
  asm("mapa.shared::cluster.u32 %0, %1, %2;" : "=r"(r) : "r"(a), "r"(rank));
  return r;
}
__device__ __forceinline__ void mbar_arrive_cluster(uint32_t b) { asm volatile("mbarrier.arrive.shared::cluster.b64 _, [%0];" ::"r"(b) : "memory"); }
__device__ __forceinline__ void mbar_wait(uint32_t b, uint32_t ph) {
  asm volatile("{.reg .pred p;\n"
               "RETRY: mbarrier.try_wait.parity.shared::cta.b64 p, [%0], %1;\n"
               "@!p bra RETRY;}" ::"r"(b), "r"(ph) : "memory");
}
__device__ __forceinline__ bool elect_one() {
  uint32_t r;
  asm volatile("{.reg .pred p; elect.sync _|p, 0xFFFFFFFF; selp.u32 %0, 1, 0, p;}" : "=r"(r));
  return r;
}
template <int ID, int N> __device__ __forceinline__ void bar_sync() { asm volatile("bar.sync %0, %1;" ::"n"(ID), "n"(N) : "memory"); }
template <int ID, int N> __device__ __forceinline__ void bar_arrive() { asm volatile("bar.arrive %0, %1;" ::"n"(ID), "n"(N) : "memory"); }
__device__ __forceinline__ void turn_wait(uint32_t id) { asm volatile("bar.sync %0, 256;" ::"r"(id) : "memory"); }
__device__ __forceinline__ void turn_pass(uint32_t id) { asm volatile("bar.arrive %0, 256;" ::"r"(id) : "memory"); }
__device__ __forceinline__ void tma2(uint32_t dst, const CUtensorMap* m, uint32_t bar, int c0, int c1) {
  asm volatile("cp.async.bulk.tensor.2d.shared::cluster.global.mbarrier::complete_tx::bytes [%0], [%1, {%3, %4}], [%2];" ::"r"(dst), "l"(m), "r"(bar), "r"(c0), "r"(c1) : "memory");
}
__device__ __forceinline__ void tma3(uint32_t dst, const CUtensorMap* m, uint32_t bar, int c0, int c1, int c2) {
  asm volatile("cp.async.bulk.tensor.3d.shared::cluster.global.mbarrier::complete_tx::bytes [%0], [%1, {%3, %4, %5}], [%2];" ::"r"(dst), "l"(m), "r"(bar), "r"(c0), "r"(c1), "r"(c2) : "memory");
}
__device__ __forceinline__ void tma2_both(uint32_t dst, const CUtensorMap* m, uint32_t bar, int c0, int c1) {
  asm volatile("cp.async.bulk.tensor.2d.shared::cluster.global.mbarrier::complete_tx::bytes.multicast::cluster [%0], [%1, {%3, %4}], [%2], %5;"
               ::"r"(dst), "l"(m), "r"(bar), "r"(c0), "r"(c1), "h"((uint16_t)3) : "memory");
}
__device__ __forceinline__ void tma3_both(uint32_t dst, const CUtensorMap* m, uint32_t bar, int c0, int c1, int c2) {
  asm volatile("cp.async.bulk.tensor.3d.shared::cluster.global.mbarrier::complete_tx::bytes.multicast::cluster [%0], [%1, {%3, %4, %5}], [%2], %6;"
               ::"r"(dst), "l"(m), "r"(bar), "r"(c0), "r"(c1), "r"(c2), "h"((uint16_t)3) : "memory");
}
__device__ __forceinline__ void bulk_prefetch(const void* src, uint32_t bytes) {
  asm volatile("cp.async.bulk.prefetch.L2.global [%0], %1;" ::"l"(src), "r"(bytes) : "memory");
}
__device__ __forceinline__ void bulk_load(uint32_t dst, const void* src, uint32_t bytes, uint32_t bar) {
  asm volatile("cp.async.bulk.shared::cluster.global.mbarrier::complete_tx::bytes [%0], [%1], %2, [%3];" ::"r"(dst), "l"(src), "r"(bytes), "r"(bar) : "memory");
}
__device__ __forceinline__ void wg_fence() { asm volatile("wgmma.fence.sync.aligned;" ::: "memory"); }
__device__ __forceinline__ void wg_commit() { asm volatile("wgmma.commit_group.sync.aligned;" ::: "memory"); }
__device__ __forceinline__ void wg_wait() { asm volatile("wgmma.wait_group.sync.aligned 0;" ::: "memory"); }
__device__ __forceinline__ uint64_t make_desc(uint32_t addr, uint32_t lbo, uint32_t sbo, uint32_t mode) {
  return (uint64_t)((addr & 0x3FFFF) >> 4) | ((uint64_t)(lbo >> 4) << 16) | ((uint64_t)(sbo >> 4) << 32) | ((uint64_t)mode << 62);
}
__device__ __forceinline__ void ldsm4(uint32_t& r0, uint32_t& r1, uint32_t& r2, uint32_t& r3, uint32_t a) {
  asm volatile("ldmatrix.sync.aligned.m8n8.x4.shared.b16 {%0, %1, %2, %3}, [%4];" : "=r"(r0), "=r"(r1), "=r"(r2), "=r"(r3) : "r"(a) : "memory");
}
__device__ __forceinline__ void ldsm4(uint32_t* r, uint32_t a) { ldsm4(r[0], r[1], r[2], r[3], a); }
__device__ __forceinline__ void ldsm2(uint32_t* r, uint32_t a) {
  asm volatile("ldmatrix.sync.aligned.m8n8.x2.shared.b16 {%0, %1}, [%2];" : "=r"(r[0]), "=r"(r[1]) : "r"(a) : "memory");
}
__device__ __forceinline__ void ldsm4t(uint32_t* r, uint32_t a) {
  asm volatile("ldmatrix.sync.aligned.m8n8.x4.trans.shared.b16 {%0, %1, %2, %3}, [%4];" : "=r"(r[0]), "=r"(r[1]), "=r"(r[2]), "=r"(r[3]) : "r"(a) : "memory");
}
__device__ __forceinline__ void ldsm2t(uint32_t* r, uint32_t a) {
  asm volatile("ldmatrix.sync.aligned.m8n8.x2.trans.shared.b16 {%0, %1}, [%2];" : "=r"(r[0]), "=r"(r[1]) : "r"(a) : "memory");
}
__device__ __forceinline__ void ld_row(uint32_t (&r)[10], uint32_t a) {
  ldsm4(r, a);
  ldsm4(r + 4, a + 64);
  ldsm2(r + 8, a + 128);
}
__device__ __forceinline__ void stsm4(uint32_t a, const uint32_t* r) {
  asm volatile("stmatrix.sync.aligned.m8n8.x4.shared.b16 [%0], {%1, %2, %3, %4};" ::"r"(a), "r"(r[0]), "r"(r[1]), "r"(r[2]), "r"(r[3]) : "memory");
}
__device__ __forceinline__ void stsm2(uint32_t a, const uint32_t* r) {
  asm volatile("stmatrix.sync.aligned.m8n8.x2.shared.b16 [%0], {%1, %2};" ::"r"(a), "r"(r[0]), "r"(r[1]) : "memory");
}
__device__ __forceinline__ void lds4(uint32_t* r, uint32_t a) {
  asm volatile("ld.shared.v4.u32 {%0, %1, %2, %3}, [%4];" : "=r"(r[0]), "=r"(r[1]), "=r"(r[2]), "=r"(r[3]) : "r"(a) : "memory");
}
__device__ __forceinline__ uint32_t lds1(uint32_t a) {
  uint32_t v;
  asm volatile("ld.shared.u32 %0, [%1];" : "=r"(v) : "r"(a) : "memory");
  return v;
}
__device__ __forceinline__ void sts1(uint32_t a, uint32_t v) { asm volatile("st.shared.u32 [%0], %1;" ::"r"(a), "r"(v) : "memory"); }
__device__ __forceinline__ void sts2(uint32_t a, uint32_t v0, uint32_t v1) { asm volatile("st.shared.v2.u32 [%0], {%1, %2};" ::"r"(a), "r"(v0), "r"(v1) : "memory"); }
__device__ __forceinline__ void mma16(float (&d)[4], uint32_t a0, uint32_t a1, uint32_t a2, uint32_t a3, uint32_t b0, uint32_t b1, const float* c) {
  asm volatile("mma.sync.aligned.m16n8k16.row.col.f32.bf16.bf16.f32 {%0, %1, %2, %3}, {%4, %5, %6, %7}, {%8, %9}, {%10, %11, %12, %13};"
               : "=f"(d[0]), "=f"(d[1]), "=f"(d[2]), "=f"(d[3])
               : "r"(a0), "r"(a1), "r"(a2), "r"(a3), "r"(b0), "r"(b1), "f"(c[0]), "f"(c[1]), "f"(c[2]), "f"(c[3]));
}
__device__ __forceinline__ void mma16(float (&d)[4], const uint32_t* a, uint32_t b0, uint32_t b1, const float* c) { mma16(d, a[0], a[1], a[2], a[3], b0, b1, c); }
__device__ __forceinline__ void mma8(float (&d)[4], uint32_t a0, uint32_t a1, uint32_t b0, const float* c) {
  asm volatile("mma.sync.aligned.m16n8k8.row.col.f32.bf16.bf16.f32 {%0, %1, %2, %3}, {%4, %5}, {%6}, {%7, %8, %9, %10};"
               : "=f"(d[0]), "=f"(d[1]), "=f"(d[2]), "=f"(d[3]) : "r"(a0), "r"(a1), "r"(b0), "f"(c[0]), "f"(c[1]), "f"(c[2]), "f"(c[3]));
}
__device__ __forceinline__ uint32_t pack2(float lo, float hi) {
  uint32_t r;
  asm volatile("cvt.rn.bf16x2.f32 %0, %1, %2;" : "=r"(r) : "f"(hi), "f"(lo));
  return r;
}
__device__ __forceinline__ float bf_lo(uint32_t w) { return __uint_as_float(w << 16); }
__device__ __forceinline__ float bf_hi(uint32_t w) { return __uint_as_float(w & 0xFFFF0000u); }
__device__ __forceinline__ float bf_round(float v) { return __uint_as_float(pack2(0.f, v)); }
__device__ __forceinline__ uint32_t fma2(uint32_t a, uint32_t b, uint32_t c) {
  uint32_t r;
  asm("fma.rn.bf16x2 %0, %1, %2, %3;" : "=r"(r) : "r"(a), "r"(b), "r"(c));
  return r;
}
__device__ __forceinline__ float ex2(float v) {
  float r;
  asm("ex2.approx.ftz.f32 %0, %1;" : "=f"(r) : "f"(v));
  return r;
}
__device__ __forceinline__ float rcp(float v) {
  float r;
  asm("rcp.approx.ftz.f32 %0, %1;" : "=f"(r) : "f"(v));
  return r;
}
__device__ __forceinline__ float rsq(float v) {
  float r;
  asm("rsqrt.approx.ftz.f32 %0, %1;" : "=f"(r) : "f"(v));
  return r;
}
__device__ __forceinline__ float sigmoid(float v) { return rcp(1.f + ex2(v * -1.4426950408889634f)); }
__device__ __forceinline__ float f32(uint32_t v) { return __uint_as_float(v); }
__device__ __forceinline__ uint32_t u32(float v) { return __float_as_uint(v); }
__device__ __forceinline__ void ld_rlx4(uint32_t* v, const void* p) {
  asm volatile("{.reg .b128 q; ld.relaxed.gpu.global.b128 q, [%4]; mov.b128 {%0, %1, %2, %3}, q;}" : "=r"(v[0]), "=r"(v[1]), "=r"(v[2]), "=r"(v[3]) : "l"(p) : "memory");
}
__device__ __forceinline__ void ld_rlx2(uint32_t* v, const void* p) {
  asm volatile("{.reg .b64 q; ld.relaxed.gpu.global.b64 q, [%2]; mov.b64 {%0, %1}, q;}" : "=r"(v[0]), "=r"(v[1]) : "l"(p) : "memory");
}
__device__ __forceinline__ uint32_t ld_rlx1(const void* p) {
  uint32_t v;
  asm volatile("ld.relaxed.gpu.global.u32 %0, [%1];" : "=r"(v) : "l"(p) : "memory");
  return v;
}
__device__ __forceinline__ void st_rlx4(void* p, uint32_t a, uint32_t b, uint32_t c, uint32_t d) {
  asm volatile("{.reg .b128 q; mov.b128 q, {%1, %2, %3, %4}; st.relaxed.gpu.global.b128 [%0], q;}" ::"l"(p), "r"(a), "r"(b), "r"(c), "r"(d) : "memory");
}
__device__ __forceinline__ void st_rlx4(void* p, const uint32_t* v) { st_rlx4(p, v[0], v[1], v[2], v[3]); }
__device__ __forceinline__ void st_rlx2(void* p, uint32_t a, uint32_t b) { asm volatile("{.reg .b64 q; mov.b64 q, {%1, %2}; st.relaxed.gpu.global.b64 [%0], q;}" ::"l"(p), "r"(a), "r"(b) : "memory"); }
__device__ __forceinline__ void st_rlx1(void* p, uint32_t v) { asm volatile("st.relaxed.gpu.global.u32 [%0], %1;" ::"l"(p), "r"(v) : "memory"); }
template <int LUT> __device__ __forceinline__ uint32_t lop3(uint32_t a, uint32_t b, uint32_t c) {
  uint32_t r;
  asm volatile("lop3.b32 %0, %1, %2, %3, %4;" : "=r"(r) : "r"(a), "r"(b), "r"(c), "n"(LUT));
  return r;
}
__device__ __forceinline__ uint32_t tag(uint32_t w, uint32_t ep) { return lop3<0xD8>(w, ep, 1u); }
__device__ __forceinline__ uint32_t neq2(uint32_t a, uint32_t b, uint32_t e) { return lop3<0x7E>(a, b, e); }
__device__ __forceinline__ uint32_t next_epoch(uint32_t e) {
  asm volatile("add.u32 %0, %0, 1;" : "+r"(e));
  return e;
}
__device__ __forceinline__ void sched_fence(uint32_t zero) {
  asm volatile("{.reg .pred p; setp.ne.u32 p, %0, 0;\nSPIN: pmevent 0; @p bra.uni SPIN;}" ::"r"(zero) : "memory");
}
__device__ __forceinline__ int pick(bool c, int a, int b) {
  int r;
  asm("{.reg .pred p; setp.ne.u32 p, %1, 0; selp.b32 %0, %2, %3, p;}" : "=r"(r) : "r"((uint32_t)c), "r"(a), "r"(b));
  return r;
}
__device__ __forceinline__ uint32_t keep(uint32_t v) { return __shfl_xor_sync(0xFFFFFFFFu, v, 2); }
__device__ __forceinline__ void wait_until(uint32_t t) {
  while ((int)(clock32() - t) < 0) {
    asm volatile("nanosleep.u32 %0;" ::"n"(NAP));
  }
}
__device__ __forceinline__ float shx(float v, int o) { return __shfl_xor_sync(0xFFFFFFFFu, v, o); }
template <int SCALE, class T> __device__ __forceinline__ T* at(T* base, uint32_t i) {
  T* r;
  asm volatile("mad.wide.u32 %0, %1, %2, %3;" : "=l"(r) : "r"(i), "n"(SCALE), "l"(base));
  return r;
}
template <uint32_t MASK> __device__ __forceinline__ bool retry(uint32_t bad, int& budget) {
  uint32_t r;
  asm volatile("{.reg .pred p, q; .reg .b32 t; add.s32 %1, %1, -1; setp.gt.s32 q, %1, 0; and.b32 t, %2, %3; setp.ne.and.u32 p, t, 0, q;\n"
               "vote.sync.any.pred p, p, 0xFFFFFFFF; selp.u32 %0, 1, 0, p;}" : "=r"(r), "+r"(budget) : "r"(bad), "n"(MASK));
  return r;
}
template <int N, int W> __device__ __forceinline__ uint32_t stale(const uint32_t (*v)[4], uint32_t ep) {
  uint32_t bad = neq2(v[0][W], v[N > 1][W], ep);
#pragma unroll
  for (int i = 2; i < N; i += 2) bad |= neq2(v[i][W], v[i + 1 < N ? i + 1 : i][W], ep);
  return bad;
}
__device__ __forceinline__ void ld_rlx4_stale(uint32_t* v, const void* p, uint32_t w, uint32_t ep) {
  asm volatile("{.reg .b128 q; .reg .pred p; .reg .b32 t; lop3.b32 t, %5, %6, 1, 0x28; setp.ne.u32 p, t, 0; mov.b128 q, {%0, %1, %2, %3};\n"
               "@p ld.relaxed.gpu.global.b128 q, [%4]; mov.b128 {%0, %1, %2, %3}, q;}"
               : "+r"(v[0]), "+r"(v[1]), "+r"(v[2]), "+r"(v[3]) : "l"(p), "r"(w), "r"(ep) : "memory");
}
template <int N, int S0, int S1, int W> __device__ __forceinline__ void gather_lazy(uint32_t (*v)[4], const uint4* p, uint32_t ep, int& budget, bool skip_last = false) {
#pragma unroll
  for (int i = 0; i < 4 * N; ++i) {
    if ((i & 3) == W) v[i >> 2][W] = N == 7 && i >= 24 && skip_last ? ep & 1u : ~ep;
    else if (N == 7 && i >= 24) v[6][i & 3] = 0;
    else asm volatile("" : "=r"(v[i >> 2][i & 3]));
  }
#pragma unroll 1
  do {
#pragma unroll
    for (int i = 0; i < N; ++i) ld_rlx4_stale(v[i], p + (i & 1) * S0 + (i >> 1) * S1, v[i][W], ep);
  } while (retry<1>(stale<N, W>(v, ep), budget));
}
template <int N, int STRIDE, int W> __device__ __forceinline__ void gather(uint32_t (*v)[4], const uint4* p, uint32_t ep, int& budget) {
#pragma unroll 1
  do {
#pragma unroll
    for (int i = 0; i < N; ++i) ld_rlx4(v[i], p + i * STRIDE);
  } while (retry<1>(stale<N, W>(v, ep), budget));
}
__device__ __forceinline__ void row_stats(float (&s)[4], float& qlo, float& qhi, const uint32_t (&x)[5][4], const uint32_t (&b)[10], int gq) {
  const float z[4] = {0.f, 0.f, 0.f, 0.f};
  float q[4][4];
#pragma unroll
  for (int i = 0; i < 5; ++i) {
    mma16(s, x[i], b[2 * i], b[2 * i + 1], i ? s : z);
#pragma unroll
    for (int e = 0; e < 4; ++e) mma8(q[e], x[i][e & 2], x[i][(e & 2) + 1], x[i][e], i ? q[e] : z);
  }
  const bool odd = gq & 1;
  qlo = (odd ? q[0][1] : q[0][0]) + (odd ? q[2][1] : q[2][0]);
  qhi = (odd ? q[1][3] : q[1][2]) + (odd ? q[3][3] : q[3][2]);
}
__device__ __forceinline__ uint32_t norm_word(float s, float q, float& mean, float& rstd) {
  mean = s * (1.f / 640.f);
  rstd = rsq(fmaxf(fmaf(q, 1.f / 640.f, -mean * mean), 0.f) + 1e-5f);
  return pack2(-mean * bf_round(rstd), rstd);
}
__device__ __forceinline__ uint32_t dup_lo(uint32_t w) { return __byte_perm(w, 0u, 0x1010); }
__device__ __forceinline__ uint32_t dup_hi(uint32_t w) { return __byte_perm(w, 0u, 0x3232); }

__device__ __forceinline__ void wgmma_n192(float (&d)[96], const uint32_t (&a)[4], uint64_t db, int add) {
  asm volatile("{.reg .pred p; setp.ne.b32 p, %101, 0; wgmma.mma_async.sync.aligned.m64n192k16.f32.bf16.bf16 "
    "{%0, %1, %2, %3, %4, %5, %6, %7, %8, %9, %10, %11, %12, %13, %14, %15, "
    "%16, %17, %18, %19, %20, %21, %22, %23, %24, %25, %26, %27, %28, %29, %30, %31, "
    "%32, %33, %34, %35, %36, %37, %38, %39, %40, %41, %42, %43, %44, %45, %46, %47, "
    "%48, %49, %50, %51, %52, %53, %54, %55, %56, %57, %58, %59, %60, %61, %62, %63, "
    "%64, %65, %66, %67, %68, %69, %70, %71, %72, %73, %74, %75, %76, %77, %78, %79, "
    "%80, %81, %82, %83, %84, %85, %86, %87, %88, %89, %90, %91, %92, %93, %94, %95}, "
    "{%96, %97, %98, %99}, %100, p, 1, 1, 1;}"
    : "+f"(d[0]), "+f"(d[1]), "+f"(d[2]), "+f"(d[3]), "+f"(d[4]), "+f"(d[5]), "+f"(d[6]), "+f"(d[7]),
      "+f"(d[8]), "+f"(d[9]), "+f"(d[10]), "+f"(d[11]), "+f"(d[12]), "+f"(d[13]), "+f"(d[14]), "+f"(d[15]),
      "+f"(d[16]), "+f"(d[17]), "+f"(d[18]), "+f"(d[19]), "+f"(d[20]), "+f"(d[21]), "+f"(d[22]), "+f"(d[23]),
      "+f"(d[24]), "+f"(d[25]), "+f"(d[26]), "+f"(d[27]), "+f"(d[28]), "+f"(d[29]), "+f"(d[30]), "+f"(d[31]),
      "+f"(d[32]), "+f"(d[33]), "+f"(d[34]), "+f"(d[35]), "+f"(d[36]), "+f"(d[37]), "+f"(d[38]), "+f"(d[39]),
      "+f"(d[40]), "+f"(d[41]), "+f"(d[42]), "+f"(d[43]), "+f"(d[44]), "+f"(d[45]), "+f"(d[46]), "+f"(d[47]),
      "+f"(d[48]), "+f"(d[49]), "+f"(d[50]), "+f"(d[51]), "+f"(d[52]), "+f"(d[53]), "+f"(d[54]), "+f"(d[55]),
      "+f"(d[56]), "+f"(d[57]), "+f"(d[58]), "+f"(d[59]), "+f"(d[60]), "+f"(d[61]), "+f"(d[62]), "+f"(d[63]),
      "+f"(d[64]), "+f"(d[65]), "+f"(d[66]), "+f"(d[67]), "+f"(d[68]), "+f"(d[69]), "+f"(d[70]), "+f"(d[71]),
      "+f"(d[72]), "+f"(d[73]), "+f"(d[74]), "+f"(d[75]), "+f"(d[76]), "+f"(d[77]), "+f"(d[78]), "+f"(d[79]),
      "+f"(d[80]), "+f"(d[81]), "+f"(d[82]), "+f"(d[83]), "+f"(d[84]), "+f"(d[85]), "+f"(d[86]), "+f"(d[87]),
      "+f"(d[88]), "+f"(d[89]), "+f"(d[90]), "+f"(d[91]), "+f"(d[92]), "+f"(d[93]), "+f"(d[94]), "+f"(d[95])
    : "r"(a[0]), "r"(a[1]), "r"(a[2]), "r"(a[3]), "l"(db), "r"(add));
}
__device__ __forceinline__ void wgmma_n48(float (&d)[24], const uint32_t (&a)[4], uint64_t db, int add) {
  asm volatile("{.reg .pred p; setp.ne.b32 p, %29, 0; wgmma.mma_async.sync.aligned.m64n48k16.f32.bf16.bf16 "
    "{%0, %1, %2, %3, %4, %5, %6, %7, %8, %9, %10, %11, %12, %13, %14, %15, "
    "%16, %17, %18, %19, %20, %21, %22, %23}, "
    "{%24, %25, %26, %27}, %28, p, 1, 1, 1;}"
    : "+f"(d[0]), "+f"(d[1]), "+f"(d[2]), "+f"(d[3]), "+f"(d[4]), "+f"(d[5]), "+f"(d[6]), "+f"(d[7]),
      "+f"(d[8]), "+f"(d[9]), "+f"(d[10]), "+f"(d[11]), "+f"(d[12]), "+f"(d[13]), "+f"(d[14]), "+f"(d[15]),
      "+f"(d[16]), "+f"(d[17]), "+f"(d[18]), "+f"(d[19]), "+f"(d[20]), "+f"(d[21]), "+f"(d[22]), "+f"(d[23])
    : "r"(a[0]), "r"(a[1]), "r"(a[2]), "r"(a[3]), "l"(db), "r"(add));
}
__device__ __forceinline__ void wgmma_n80(float (&d)[40], const uint32_t (&a)[4], uint64_t db, int add) {
  asm volatile("{.reg .pred p; setp.ne.b32 p, %45, 0; wgmma.mma_async.sync.aligned.m64n80k16.f32.bf16.bf16 "
    "{%0, %1, %2, %3, %4, %5, %6, %7, %8, %9, %10, %11, %12, %13, %14, %15, "
    "%16, %17, %18, %19, %20, %21, %22, %23, %24, %25, %26, %27, %28, %29, %30, %31, "
    "%32, %33, %34, %35, %36, %37, %38, %39}, "
    "{%40, %41, %42, %43}, %44, p, 1, 1, 1;}"
    : "+f"(d[0]), "+f"(d[1]), "+f"(d[2]), "+f"(d[3]), "+f"(d[4]), "+f"(d[5]), "+f"(d[6]), "+f"(d[7]),
      "+f"(d[8]), "+f"(d[9]), "+f"(d[10]), "+f"(d[11]), "+f"(d[12]), "+f"(d[13]), "+f"(d[14]), "+f"(d[15]),
      "+f"(d[16]), "+f"(d[17]), "+f"(d[18]), "+f"(d[19]), "+f"(d[20]), "+f"(d[21]), "+f"(d[22]), "+f"(d[23]),
      "+f"(d[24]), "+f"(d[25]), "+f"(d[26]), "+f"(d[27]), "+f"(d[28]), "+f"(d[29]), "+f"(d[30]), "+f"(d[31]),
      "+f"(d[32]), "+f"(d[33]), "+f"(d[34]), "+f"(d[35]), "+f"(d[36]), "+f"(d[37]), "+f"(d[38]), "+f"(d[39])
    : "r"(a[0]), "r"(a[1]), "r"(a[2]), "r"(a[3]), "l"(db), "r"(add));
}

__device__ __forceinline__ constexpr int wo_off(int i) { return (i < 4 ? 8 + i : i - 4) * WO; }
__device__ __forceinline__ void load_stage(const Params& P, uint32_t sb, int st, int j, int g, int rank) {
  const uint32_t fb = sb + OFF_BAR + 8 * (B_FULL + (st & 3)), a = sb + (st & 3) * STAGE;
  mbar_expect_tx(fb, STAGE);
  tma2(a, &P.xa, fb, 640 * rank + 64 * st, 128 * j);
  tma3_both(a + STAGE_A + rank * (STAGE_B0 / 2), &P.w0, fb, 80 * g, 64 * st + 32 * rank, 0);
  tma3_both(a + STAGE_A + STAGE_B0 + rank * (STAGE_B1 / 2), &P.w1, fb, 80 * g + 64, 64 * st + 32 * rank, 0);
}

__device__ __forceinline__ void run_producer(const Params& P, uint8_t* sm, uint32_t sb, int b, uint32_t t0) {
  const int rank = b & 1, g = (b >> 1) & 7, j = b >> 4;
  const uint32_t bar = sb + OFF_BAR;
#pragma unroll 1
  for (int st = 1; st < 10; ++st) {
    if (st == 2) {
      wait_until(t0 + WPF_AT);
      if (elect_one()) bulk_prefetch(P.wqkv + (128 + 4 * b) * 1920, 15360);
      bar_sync<NB_GO, 160>();
    }
    if (st == 9) bar_sync<NB_HELP, 128>();
    mbar_wait(bar + 8 * (B_EMPTY + (st & 3)), (((st + 1) >> 2) + 1) & 1);
    if (elect_one()) {
      load_stage(P, sb, st, j, g, rank);
      const int k = st - LMPF_AT;
      if ((uint32_t)k < 5u) bulk_prefetch(P.wmod + (5 * b + k) * 3840 + 1280, 5120);
      if (st == 7) bulk_prefetch(P.wo + b * 3200, 6400);
    }
  }
  TSTAMP(1);
#pragma unroll 1
  for (int i = 0; i < 8; ++i) {
    if (i < 2 || i == 4 || i == 7) mbar_wait(bar + 8 * (B_EMPTY + (i < 2 ? 2 + i : i & 1)), i == 0);
    if (elect_one()) {
      const uint32_t fb = bar + 8 * (i ? B_WO1 : B_WO0), a = sb + (i < 4 ? 8 + i : i - 4) * WO;
      if (i == 0) {
        mbar_expect_tx(bar + 8 * B_XS, 25600);
        tma2(sb + OFF_LM, &P.wm, bar + 8 * B_XS, 1280 + 80 * (b & 31), 160 * (b >> 5));
      }
      if (i < 2) mbar_expect_tx(fb, i ? 7 * 12800 : 12800);
      if ((i & 1) == rank) {
        const int k0 = 80 * (i ? i - (i <= g) : g);
        tma3_both(a, &P.woa, fb, 80 * g, k0, 0);
        tma2_both(a + 10240, &P.wob, fb, 80 * g + 64, k0);
      }
    }
  }
  TSTAMP(3);
  if (b < N_FFN) {
    if (elect_one()) {
      mbar_expect_tx(bar + 8 * B_ACT, 1024);
      mbar_expect_tx(bar + 8 * B_FFN, 40960);
    }
    mbar_wait(bar + 8 * B_GO, 1);
    uint32_t next = clock32();
#pragma unroll 1
    for (int i = 0; i < 6; ++i) {
      if (i == 3) bar_sync<NB_LM, 128>();
      wait_until(next);
      next += FFN_GAP;
      if (elect_one())
        tma3(sb + OFF_FFN + 10240 * i, &P.wg + (i >> 1), bar + 8 * (i < 4 ? B_FFN : B_XS), i < 4 ? 32 * (b >> 1) : 0, i < 4 ? 0 : 16 * b, i < 4 ? 2 * rank + (i & 1) : 5 * (i & 1));
    }
  }
  TSTAMP(4);
}

__device__ __forceinline__ void run_helper(const Params& P, uint8_t* sm, uint32_t sb, int b, int hw, uint32_t ep, int budget, uint32_t poll_at) {
  const int h = threadIdx.x - 256, lane = h & 31, gq = lane >> 2, t = lane & 3, rank = b & 1, g = (b >> 1) & 7, j = b >> 4;
  const uint32_t bar = sb + OFF_BAR, prm = sb + OFF_PRM;
  uint4* const box = P.sc + b * BOX;
  const bool main20 = lane < 20;
  const int fin = 128 * (b >> 4) + 16 * ((b >> 2) & 3) + 2 * (b & 3) + (lane & 1) + 32 * (lane & 2) + 2 * (lane & 4);
  const int which = main20 ? 2 - hw : 3, fsl = (fin * 205) >> 14;
  const int q4 = main20 ? lane : hw < 2 ? min(10 * hw + lane - 20, 19) : (fin - 80 * fsl) >> 2;
  uint32_t wr[2];
  asm volatile("ld.global.nc.v2.u32 {%0, %1}, [%2];" : "=r"(wr[0]), "=r"(wr[1]) : "l"(P.wr + 80 * g + 4 * q4));
  uint32_t cw;
  asm volatile("ld.global.nc.u32 %0, [%1];" : "=r"(cw) : "l"(P.c + 160 * (b >> 5) + 2 * min(h, 79)));
  sts1(sb + OFF_SILU + 4 * min(h, 79), pack2(bf_lo(cw) * sigmoid(bf_lo(cw)), bf_hi(cw) * sigmoid(bf_hi(cw))));
  if (h < 4) sts1(prm + R_ONE + 4 * h, 0x3F803F80u);
  wait_until(poll_at);
  {
    uint32_t v[4][4];
    const int h80 = min(h, 79);
    const uint4* src = at<16>(P.sc, (h80 >> 2) * BOX + 4 * j + (h80 & 3));
#pragma unroll 1
    do {
#pragma unroll
      for (int i = 0; i < 4; ++i) ld_rlx4(v[i], src + i * 20 * BOX);
    } while (retry<~0u>(stale<4, 2>(v, ep), budget));
#pragma unroll
    for (int i = 0; i < 4; ++i) sts2(sb + OFF_C1 + 16 * h80 + 1280 * (i & 1) + (i < 2 ? 8 : 0), v[i][0], v[i][1]);
    mbar_arrive(bar + 8 * B_TAB);
  }
  TSTAMP(3);
  bar_sync<NB_GO, 160>();
  {
    const char* src = hw == 2 ? at<128>(reinterpret_cast<const char*>(P.wdown), 160 * b + lane)
                              : at<128>(reinterpret_cast<const char*>(hw ? P.wup : P.wgate), (160 * (b & 3) + lane) * 27 + (b >> 2));
    uint4* slot = at<16>(box + M_HALO, h);
    uint32_t next = clock32() + TOUCH_AT + hw * (TOUCH_GAP / 3);
#pragma unroll 1
    for (int i = 0; i < 5; ++i) {
      wait_until(next);
      next += TOUCH_GAP;
      if (b < N_FFN) asm volatile("cp.async.cg.shared.global.L2::128B [%0], [%1], 16;" ::"r"(sb + OFF_SINK + 16 * h), "l"(src) : "memory");
      src += hw == 2 ? 4096 : 32 * 3456;
      if (i < 4) {
        st_rlx4(slot, ~ep, ~ep, ~ep, ~ep);
        st_rlx4(slot + 96, ~ep, ~ep, ~ep, ~ep);
      }
      slot += 192;
    }
  }
  bar_sync<NB_HELP, 128>();
  TSTAMP(5);

  {
    float d0[4] = {0.f, 0.f, 0.f, 0.f}, d1[4] = {0.f, 0.f, 0.f, 0.f};
    uint32_t wa = sb + OFF_LM + (8 * (lane >> 4) + (lane & 7)) * 160 + 64 * hw + (lane & 8) * 2, sa = sb + OFF_SILU + (lane >> 3) * 16;
    mbar_wait(bar + 8 * B_XS, 1);
    {
      uint32_t hv[2][4] = {};
      const int q = min(2 * hw, 3);
      const uint4* const src = at<16>(box + (M_HALO - 16 * BOX), 32 * q + lane);
      mbar_wait(bar + 8 * B_EMPTY, 0);
      wait_until(clock32() + HALO_GAP);
      if (j > 0) gather<2, 32, 0>(hv, src, ep, budget);
      stsm4(sb + OFF_H + 512 * q + 16 * lane, hv[0]);
      stsm4(sb + OFF_H + 512 * q + 16 * lane + 512, hv[1]);
      bar_arrive<NB_HALO, 128>();
      if (j > 0) TSTAMP(4);
    }
    mbar_wait(bar + 8 * (B_EMPTY + 1), 0);
    TSTAMP(6);
#pragma unroll 1
    for (int u = 0; u < 5; ++u) {
      uint32_t a[4][4], s[4];
      ldsm4(s, sa);
#pragma unroll
      for (int i = 0; i < 4; ++i) ldsm4t(a[i], wa + (i >> 1) * 2560 + (i & 1) * 32);
      mma16(d0, a[0], s[0], s[1], d0);
      mma16(d1, a[1], s[0], s[1], d1);
      mma16(d0, a[2], s[2], s[3], d0);
      mma16(d1, a[3], s[2], s[3], d1);
      wa += 5120;
      sa += 64;
    }
    const float v = t & 2 ? (t & 1 ? d1[2] : d1[0]) : (t & 1 ? d0[2] : d0[0]);
    if (32 * hw + 8 * t < 80) st_rlx1(at<4>(box + M_LATE, 32 * hw + 8 * t + gq), tag(u32(v), ep));
  }
  if (b < N_FFN) {
    if (h == 0) mbar_expect_tx(bar + 8 * B_XS, 20480);
    bar_arrive<NB_LM, 128>();
  }
  TSTAMP(7);
  wait_until(clock32() + LATE_GAP);
  {
    uint32_t v[4][4];
    const uint4* src = at<16>(P.sc + M_LATE, (8 * which + (main20 || hw < 2 ? g : fsl & 7)) * BOX + q4);
#pragma unroll 1
    do {
#pragma unroll
      for (int i = 0; i < 4; ++i) ld_rlx4(v[i], src + i * 32 * BOX);
    } while (retry<1>(stale<4, 0>(v, ep) | stale<4, 1>(v, ep) | stale<4, 2>(v, ep) | stale<4, 3>(v, ep), budget));
    const uint32_t one = which == 2 ? 0x3F803F80u : 0u;
    uint32_t w[2], pw[2];
#pragma unroll
    for (int e = 0; e < 2; ++e) {
      w[e] = fma2(pack2(f32(v[0][2 * e]) + f32(v[1][2 * e]) + f32(v[2][2 * e]) + f32(v[3][2 * e]),
                        f32(v[0][2 * e + 1]) + f32(v[1][2 * e + 1]) + f32(v[2][2 * e + 1]) + f32(v[3][2 * e + 1])), 0x3F803F80u, one);
      pw[e] = fma2(w[e], wr[e], 0x80008000u);
    }
    const uint32_t dst = prm + (main20 || hw < 2 ? 160 * which + 8 * q4 : R_FIN + 4 * (lane & 6));
    sts2(dst, w[0], w[1]);
    sts2(dst + 800, pw[0], pw[1]);
    float s = main20 ? bf_lo(pw[0]) + bf_hi(pw[0]) + bf_lo(pw[1]) + bf_hi(pw[1]) : 0.f;
#pragma unroll
    for (int o = 16; o > 0; o >>= 1) s += shx(s, o);
    sts1(sb + OFF_KEY + 64 + 4 * hw, u32(s));
    mbar_arrive(bar + 8 * B_TAB);
    mbar_wait(bar + 8 * B_TAB, 1);
  }
  TSTAMP(8);

  uint32_t ckey = 0;
  uint4* const odst = reinterpret_cast<uint4*>(P.out + (256 * j + rank) * 640 + 80 * g);
  if (hw == 0) {
    const uint32_t tile = min(4 * (lane & 3) + (lane >> 3), 9) * 16;
    uint32_t c1[4], sv[4], gb[4], x[4];
    ldsm4(c1, prm + R_C1 + tile);
    ldsm4(sv, prm + R_SB + tile);
    ldsm4(gb, prm + (lane & 4 ? R_GB + tile : R_ONE));
    const uint32_t bc = lds1(sb + OFF_KEY + 68), keep = gq & 4 ? ~0u : 0u;
    uint4* const cdst = at<16>(P.sc + M_CAND, (b - rank + (lane >> 4)) * BOX + 2 * (lane & 12) + 4 * rank + (lane & 3));
    uint32_t crow;
    {
      bar_sync<NB_KEY, 288>();
      uint32_t k0, k1;
      asm volatile("ld.shared.v2.u32 {%0, %1}, [%2];" : "=r"(k0), "=r"(k1) : "r"(sb + OFF_KEY + 8 * (lane & 7)) : "memory");
      ckey = __reduce_max_sync(0xFFFFFFFFu, k0);
      crow = (~ckey >> 1) & 127;
      TSTAMP(9);
      ldsm4(x, sb + OFF_X2 + crow * 176 + tile);
      const uint32_t nw = __shfl_sync(0xFFFFFFFFu, k1, crow >> 4), rs = dup_hi(nw), nm = dup_lo(nw);
#pragma unroll
      for (int e = 0; e < 4; ++e) x[e] = fma2(gb[e], fma2(fma2(x[e], rs, nm), c1[e], sv[e]), x[e] & keep);
      st_rlx4(cdst, tag(x[0], ep), x[1], gq == 2 ? ckey : x[2], gq == 2 ? bc : x[3]);
    }
    bar_arrive<NB_PUB, 288>();
    TSTAMP(10);
    bar_sync<NB_OUT + 1, 160>();
    uint32_t next = clock32() + OUT_AT;
#pragma unroll 1
    for (int u = 0; u < 8; ++u) {
      if (u == 4) {
        bar_sync<NB_OUT, 160>();
        next = clock32();
      }
      wait_until(next);
      next += OUT_GAP;
      if (u != crow >> 4 && elect_one())
        asm volatile("cp.async.bulk.tensor.2d.global.shared::cta.bulk_group [%0, {%2, %3}], [%1];"
                     ::"l"(&P.om), "r"(sb + OFF_OUT + 2560 * u), "r"(640 * rank + 80 * g), "r"(128 * j + 16 * u) : "memory");
    }
    asm volatile("cp.async.bulk.commit_group;" ::: "memory");
    TSTAMP(11);
  } else {
    if (b >= 80 || hw == 2) return;
    bar_sync<NB_WIN, 64>();
  }
  uint32_t m[7][4], wkey = lds1(sb + OFF_KEY + 80);
  if (b >= N_FFN) {
    gather<1, 0, 0>(m, at<64>(P.sc + M_CAND + 16, (lane & 14) * (2 * BOX) + (lane & 1)), ep, budget);
    wkey = __reduce_max_sync(0xFFFFFFFFu, m[0][2]);
  }
  const uint32_t wtok = ~wkey & 2047;
  TSTAMP(12);
  if (hw == 0) {
    const uint32_t u = (~ckey >> 5) & 7, skip = ckey == wkey ? (~ckey >> 1) & 15 : 16;
#pragma unroll
    for (int i = 0; i < 5; ++i) {
      const uint32_t v = lane + 32 * i, r = (v * 205) >> 11;
      if (r != skip) *at<16>(odst, 2560 * u + v + 150 * r) = *reinterpret_cast<const uint4*>(sm + OFF_OUT + 2560 * u + 16 * v);
    }
    st_rlx1(at<4>(box + M_EPOCH, lane), ep);
    asm volatile("cp.async.bulk.wait_group.read 0;" ::: "memory");
    TSTAMP(15);
    TALIGN(1);
    return;
  } else {
    const int cn = fin - 80 * fsl;
    gather<1, 0, 0>(m, at<16>(P.sc + M_CAND, (16 * (wtok >> 8) + (lane & 8 ? 2 * (lane & 7) : 2 * fsl + 1)) * BOX + 4 * (wtok & 1) +
                                             (lane & 8 ? 16 : 8 * (cn >> 5) + ((cn >> 1) & 3))), ep, budget);
    const uint32_t bw = cn & 16 ? (cn & 8 ? m[0][3] : m[0][2]) : (cn & 8 ? m[0][1] : m[0][0]);
    const uint32_t gw = lds1(prm + R_FIN + 4 * (lane & 6) + 4 * (b & 1));
    float r = f32(m[0][3]);
#pragma unroll
    for (int o = 1; o < 8; o <<= 1) r += shx(r, o);
    r = __shfl_sync(0xFFFFFFFFu, r, 8) + f32(wkey >> 31 ? wkey & 0x7FFFF800u : ~wkey | 0x7FFu);
    const float sg = bf_round(sigmoid(bf_round(r))), gv = lane & 1 ? bf_hi(gw) : bf_lo(gw), bv = lane & 1 ? bf_hi(bw) : bf_lo(bw);
    __nv_bfloat16* const dst = at<2>(P.out, wtok * 640 + fin);
    const uint4* const src = at<16>(P.sc + M_YP, (4 * (lane >> 3) + ((b >> 2) & 3)) * BOX + 32 * j + 8 * (b & 3) + (lane & 7));
    TSTAMP(13);
    bar_sync<NB_YP, 64>();
    wait_until(clock32() + YP_GAP);
    gather_lazy<7, 16 * BOX, 32 * BOX, 0>(m, src, ep, budget, lane >= 24);
    TSTAMP(14);
    float y[4];
#pragma unroll
    for (int e = 0; e < 4; ++e)
      y[e] = ((f32(m[0][e]) + f32(m[1][e])) + (f32(m[2][e]) + f32(m[3][e]))) + ((f32(m[4][e]) + f32(m[5][e])) + f32(m[6][e]));
    const bool u1 = lane & 2, u2 = lane & 4;
    const float e0 = (u1 ? y[1] : y[0]) + shx(u1 ? y[0] : y[1], 2), e1 = (u1 ? y[3] : y[2]) + shx(u1 ? y[2] : y[3], 2);
    float e = (u2 ? e1 : e0) + shx(u2 ? e0 : e1, 4);
    e += shx(e, 8);
    e += shx(e, 16);
    asm volatile("{.reg .pred p; setp.lt.u32 p, %2, 8; @p st.global.b16 [%0], %1;}"
                 ::"l"(dst), "h"((uint16_t)pack2(fmaf(gv, bf_round(bf_round(e) * sg), bv), 0.f)), "r"(lane) : "memory");
  }
  TSTAMP(15);
}

#define ACC(part, i, e) ((i) < 8 ? accA[32 * (part) + 4 * ((i) & 7) + (e)] : accB[8 * (part) + 4 * ((i) & 1) + (e)])
__device__ __forceinline__ constexpr int kpos(int i) { return i == 2 ? 8 : i == 7 ? 9 : i - (i > 2) - (i > 7); }

__device__ __forceinline__ void run_consumer(const Params& P, uint8_t* sm, uint32_t sb, int b, int warp, uint32_t ep, int budget) {
  const int tid = threadIdx.x, lane = tid & 31, gq = lane >> 2, t = lane & 3, p = warp >> 2, wq = warp & 3, rb = warp ^ 4;
  const int rank = b & 1, g = (b >> 1) & 7, j = b >> 4;
  const uint32_t bar = sb + OFF_BAR;
  uint4* const box = P.sc + b * BOX;
  const float z4[4] = {0.f, 0.f, 0.f, 0.f};

  uint32_t nrm[4];
  {
    uint32_t x[5][4], ones[10];
#pragma unroll
    for (int i = 0; i < 10; ++i) ones[i] = 0x3F803F80u;
    uint4* const dst = at<8>(box + M_ST1, tid >> 4);
    mbar_wait(bar + 8 * B_XS, 0);
    TSTAMP(4);
#pragma unroll
    for (int i = 0; i < 5; ++i) lds4(x[i], sb + OFF_XS + (tid >> 4) * 1280 + (lane & 15) * 16 + 256 * i);
    float s[4], qlo, qhi, mean, rstd;
    row_stats(s, qlo, qhi, x, ones, gq);
    const float q = __shfl_sync(0xFFFFFFFFu, qlo + qhi, 4 * gq + (gq >> 1));
    float v = t & 1 ? q : s[0] + s[2];
    v += shx(v, 4);
    v += shx(v, 8);
    const uint32_t nw = norm_word(v, shx(v, 1), mean, rstd);
    if ((lane & 15) == 0) st_rlx2(dst, nw, ep);
    TSTAMP(5);
    asm volatile("setmaxnreg.inc.sync.aligned.u32 224;");
  }

  float accA[96], accB[24];
#pragma unroll
  for (int i = 0; i < 96; ++i) asm volatile("" : "=f"(accA[i]));
#pragma unroll
  for (int i = 0; i < 24; ++i) asm volatile("" : "=f"(accB[i]));
  uint32_t xr[5][4];
#pragma unroll
  for (int i = 0; i < 20; ++i) asm volatile("" : "=r"(xr[i >> 2][i & 3]));
  const uint32_t turn = keep(NB_TURN + (tid >> 7)), pass = keep(NB_TURN + 1 - (tid >> 7));
  uint4* const opub = reinterpret_cast<uint4*>(__shfl_xor_sync(0xFFFFFFFFu, reinterpret_cast<uintptr_t>(at<16>(box + M_O, tid ^ 2)), 2));
  const uint4* src[7];
  const int l2 = lane ^ 2;
  const uint32_t ha = keep(sb + OFF_H + rb * 2560 + 16 * l2), lo = keep(sb + OFF_L + rb * 1280 + 16 * l2);
  const uint32_t va = keep(sb + OFF_H + 1280 + (rb + ((lane >> 3) & 1)) * 2560 + (lane >> 4) * 128 + (l2 & 7) * 16);
  const uint32_t M = keep((2 * (t ^ 2) > gq ? 0xFFFFu : 0u) | (2 * (t ^ 2) + 1 > gq ? 0xFFFF0000u : 0u)), gk = keep(g + (tid >> 9));
  {
    uint32_t la = sb + (16 * rb + (lane & 15)) * 128 + (((lane >> 4) ^ (lane & 7)) << 4), c1a = sb + OFF_C1 + 16 * t;
    const uint32_t rel = keep(map_to_cta(bar + 8 * B_EMPTY + 16, lane & 1)), y0 = keep(8 * ((5 * g >> 2) + 1) + (tid >> 9));
    const bool two = (ha & 0x1E0) == 0;
    const uint64_t dbase = make_desc(sb + STAGE_A, 4096, 1024, 1);
    uint64_t d0 = dbase;
    uint32_t raw[4][4], cw[4][4], y = 8;
    int add = 0;
    if (p == 1) turn_pass(pass);
    {
      const uint4* const src = at<8>(P.sc + M_ST1, (16 * j + 2 * rb) * 2 * BOX + 2 * gq + rank);
      mbar_wait(bar + 8 * B_FULL, 0);
#pragma unroll
      for (int k = 0; k < 4; ++k) ldsm4(raw[k], la ^ (32 * k));
      uint32_t n0[2], n1[2];
#pragma unroll 1
      do {
        ld_rlx2(n0, src);
        ld_rlx2(n1, src + BOX);
      } while (retry<~0u>(neq2(n0[1], n1[1], ep), budget));
      TSTAMP(6);
      mbar_wait(bar + 8 * B_TAB, 0);
#pragma unroll
      for (int k = 0; k < 4; ++k) lds4(cw[k], c1a + 64 * k);
      if (warp == 0) bar_arrive<NB_GO, 160>();
      nrm[0] = dup_hi(n0[0]); nrm[1] = dup_hi(n1[0]); nrm[2] = dup_lo(n0[0]); nrm[3] = dup_lo(n1[0]);
    }
    TSTAMP(7);
#pragma unroll 1
    for (;;) {
      uint32_t af[4][4];
      c1a += 256;
#pragma unroll
      for (int k = 0; k < 16; ++k) raw[k >> 2][k & 3] = fma2(raw[k >> 2][k & 3], nrm[k & 1], nrm[2 + (k & 1)]);
      wg_wait();
      if (two) mbar_arrive_cluster(rel ^ (y & 24));
#pragma unroll
      for (int k = 0; k < 16; ++k) af[k >> 2][k & 3] = fma2(raw[k >> 2][k & 3], cw[k >> 2][(k >> 1) & 1], cw[k >> 2][2 + ((k >> 1) & 1)]);
#pragma unroll
      for (int k = 0; k < 4; ++k) lds4(cw[k], c1a + 64 * k);
      wg_fence();
      turn_wait(turn);
      constexpr uint64_t D1 = (STAGE_B0 >> 4) + ((uint64_t)64 << 16) - ((uint64_t)256 << 16) + ((uint64_t)16 << 32) - ((uint64_t)64 << 32) + ((uint64_t)2 << 62);
#pragma unroll
      for (int k = 0; k < 4; ++k) {
        wgmma_n192(accA, af[k], d0 + ((k >> 1) * (STAGE_B0 / 2) + (k & 1) * 2048 >> 4), k ? 1 : add);
        if (PASS1 == 2 * k) turn_pass(pass);
        wgmma_n48(accB, af[k], d0 + (D1 + ((k >> 1) * (STAGE_B1 / 2) + (k & 1) * 512 >> 4)), k ? 1 : add);
        if (PASS1 == 2 * k + 1) turn_pass(pass);
      }
      wg_commit();
      if (__any_sync(0xFFFFFFFFu, y - y0 < 16u)) {
#pragma unroll
        for (int i = 0; i < 5; ++i) {
          const uint32_t k = 160 * g + 32 * i + 128 - 16 * y;
          if (k < 128u) ldsm4(xr[i], la ^ k);
        }
      }
      if (y == 80) break;
      const bool wrap = (uint32_t)d0 == (uint32_t)dbase + (3 * STAGE >> 4);
      la += wrap ? -3 * STAGE : STAGE;
      d0 = wrap ? dbase : d0 + (STAGE >> 4);
      add = 1;
      mbar_wait(bar + (y & 24), (y >> 5) & 1);
#pragma unroll
      for (int k = 0; k < 4; ++k) ldsm4(raw[k], la ^ (32 * k));
      y += 8;
    }
    wg_wait();
    if (two) mbar_arrive_cluster(rel - 8);
  }
  TSTAMP(8);

  uint32_t o[5][4];
  {
    uint32_t hi[20], vl[10], kl[10], kh[10], vv[20], qf[4][4], qs[4][2];
#pragma unroll
    for (int i = 0; i < 10; ++i) {
      hi[kpos(i)] = pack2(ACC(1, i, 2), ACC(1, i, 3));
      hi[10 + i] = pack2(ACC(2, i, 2), ACC(2, i, 3));
    }
#pragma unroll
    for (int q = 0; q < 5; ++q) hi[4 * q] = tag(hi[4 * q], ep);
    if (rb == 7) {
#pragma unroll
      for (int q = 0; q < 5; ++q) st_rlx4(opub + (M_HALO - M_O - 96 + 32 * q), hi + 4 * q);
    }
    TSTAMP(29);
#pragma unroll
    for (int i = 0; i < 10; ++i) kl[kpos(i)] = pack2(ACC(1, i, 0), ACC(1, i, 1));
#pragma unroll
    for (int hd = 0; hd < 4; ++hd) {
      const int f0 = 5 * (hd >> 1) + 3 * (hd & 1), sg = 5 * (hd >> 1) + 2;
      const bool mine = (t >> 1) == (hd & 1);
#pragma unroll
      for (int e = 0; e < 4; ++e) qf[hd][e] = pack2(ACC(0, f0 + (e >> 1), 2 * (e & 1)), ACC(0, f0 + (e >> 1), 2 * (e & 1) + 1));
#pragma unroll
      for (int e = 0; e < 2; ++e) {
        if (!(hd & 1)) qs[hd + 1][e] = pack2(ACC(0, sg, 2 * e), ACC(0, sg, 2 * e + 1));
        qs[hd][e] = mine ? qs[hd | 1][e] : 0u;
      }
    }
    sched_fence(P.zero);
#pragma unroll
    for (int q = 0; q < 5; ++q) stsm4(ha + 2560 + 512 * q, hi + 4 * q);
#pragma unroll
    for (int i = 0; i < 10; ++i) vl[i] = pack2(ACC(2, i, 0), ACC(2, i, 1));
    stsm4(lo, vl);
    stsm4(lo + 512, vl + 4);
    stsm2(lo + 1024, vl + 8);
    __syncwarp();
    if (lane == 0) mbar_arrive(bar + 8 * B_HALO);
    float S0[4][4], S1[4][4], S2[4][4];
    ldsm4t(vl, lo);
    ldsm4t(vl + 4, lo + 512);
    ldsm2t(vl + 8, lo + 1024);
#pragma unroll
    for (int hd = 0; hd < 4; ++hd) {
      mma16(S1[hd], qf[hd], kl[2 * hd], kl[2 * hd + 1], z4);
      mma16(S2[hd], qf[hd], hi[2 * hd], hi[2 * hd + 1], z4);
    }
#pragma unroll
    for (int hd = 0; hd < 4; ++hd) {
      mma8(S1[hd], qs[hd][0], qs[hd][1], kl[8 + (hd >> 1)], S1[hd]);
      mma8(S2[hd], qs[hd][0], qs[hd][1], hi[8 + (hd >> 1)], S2[hd]);
    }
    {
      const uint4* const lower = opub - 2 * BOX * g;
      const uint4* const upper = lower + 2 * BOX;
#pragma unroll
      for (int i = 0; i < 7; ++i) src[i] = i < gk ? lower : upper;
    }
    TSTAMP(9);
    mbar_wait(bar + 8 * B_HALO, 0);
    if (rb == 0) bar_sync<NB_HALO, 128>();
    TSTAMP(10);
    ldsm4(kh, ha);
    ldsm4(kh + 4, ha + 512);
    ldsm2(kh + 8, ha + 1024);
#pragma unroll
    for (int i = 0; i < 5; ++i) ldsm4t(vv + 4 * i, va + 256 * i);
    const float SC = 0.22360679774997896f * 1.4426950408889634f, ev = (j | rb) == 0 ? -1e9f / 0.22360679774997896f : 0.f;
    const float e4[4] = {ev, ev, ev, ev};
#pragma unroll
    for (int hd = 0; hd < 4; ++hd) mma16(S0[hd], qf[hd], kh[2 * hd], kh[2 * hd + 1], e4);
#pragma unroll
    for (int hd = 0; hd < 4; ++hd) mma8(S0[hd], qs[hd][0], qs[hd][1], kh[8 + (hd >> 1)], S0[hd]);
    const bool up0 = M == ~0u, up1 = M != 0;
    uint32_t pp[4][2];
    {
      float a[8][2], mx[8];
#pragma unroll
      for (int hd = 0; hd < 4; ++hd) {
        a[2 * hd][0] = up0 ? S0[hd][0] : S1[hd][0];
        a[2 * hd][1] = up1 ? S0[hd][1] : S1[hd][1];
        a[2 * hd + 1][0] = up0 ? S1[hd][2] : S2[hd][2];
        a[2 * hd + 1][1] = up1 ? S1[hd][3] : S2[hd][3];
      }
#pragma unroll
      for (int i = 0; i < 8; ++i) mx[i] = fmaxf(a[i][0], a[i][1]);
#pragma unroll
      for (int s = 1; s < 4; s <<= 1) {
#pragma unroll
        for (int i = 0; i < 8; ++i) mx[i] = fmaxf(mx[i], shx(mx[i], s));
      }
#pragma unroll
      for (int i = 0; i < 8; ++i) {
        const float ms = mx[i] * -SC;
        pp[i >> 1][i & 1] = pack2(ex2(fmaf(a[i][0], SC, ms)), ex2(fmaf(a[i][1], SC, ms)));
      }
    }
    float L[4][4], O[4][3][4];
#pragma unroll
    for (int hd = 0; hd < 4; ++hd) mma8(L[hd], pp[hd][0], pp[hd][1], 0x3F803F80u, z4);
#pragma unroll
    for (int hd = 0; hd < 4; ++hd) {
      const uint32_t p0 = pp[hd][0] & M, p2 = pp[hd][0] & ~M, p3 = pp[hd][1] & M, p5 = pp[hd][1] & ~M;
      const uint32_t z0 = pp[hd][0] & P.zero, z1 = pp[hd][1] & P.zero;
#pragma unroll
      for (int e = 0; e < 3; ++e) {
        const int f = 5 * (hd >> 1) + 2 * (hd & 1) + e;
        mma16(O[hd][e], p0, z0, z1, p5, vv[2 * f], vv[2 * f + 1], z4);
      }
#pragma unroll
      for (int e = 0; e < 3; ++e) mma8(O[hd][e], p2, p3, vl[5 * (hd >> 1) + 2 * (hd & 1) + e], O[hd][e]);
    }
    const bool odd = t >> 1;
#pragma unroll
    for (int hp = 0; hp < 2; ++hp) {
      const float (&A)[3][4] = O[2 * hp];
      const float (&B)[3][4] = O[2 * hp + 1];
#pragma unroll
      for (int e = 0; e < 2; ++e) {
        const float ra = rcp(L[2 * hp][2 * e]), rc = rcp(L[2 * hp + 1][2 * e]), rm = odd ? rc : ra;
        uint32_t* const d = &o[0][0] + 10 * hp + e;
        d[0] = pack2(A[0][2 * e] * ra, A[0][2 * e + 1] * ra);
        d[2] = pack2(A[1][2 * e] * ra, A[1][2 * e + 1] * ra);
        d[4] = pack2((odd ? B[0][2 * e] : A[2][2 * e]) * rm, (odd ? B[0][2 * e + 1] : A[2][2 * e + 1]) * rm);
        d[6] = pack2(B[1][2 * e] * rc, B[1][2 * e + 1] * rc);
        d[8] = pack2(B[2][2 * e] * rc, B[2][2 * e + 1] * rc);
      }
      if (hp == 0) {
#pragma unroll
        for (int s = 0; s < 2; ++s) {
          o[s][0] = tag(o[s][0], ep);
          st_rlx4(opub + 256 * s, o[s]);
        }
        sched_fence(P.zero);
        if (p == 1) bar_arrive<NB_PV, 256>();
      }
    }
#pragma unroll
    for (int s = 2; s < 5; ++s) o[s][0] = tag(o[s][0], ep);
  }
  TSTAMP(11);

  float acc[40];
#pragma unroll
  for (int i = 0; i < 40; ++i) asm volatile("" : "=f"(acc[i]));
  uint32_t ga[10], pb[10], uw;
  uint4* const sdst = at<16>(box + M_ST2, 16 * rb + gq);
  const uint32_t prow = sb + OFF_PRM + (lane >> 3) * 16;
  {
    const uint64_t dw = make_desc(sb, 5120, 512, 2);
    uint32_t in[3][7][4];
    st_rlx4(opub + 256 * 2, o[2]);
    mbar_wait(bar + 8 * B_WO0, 0);
    if (p == 0) bar_sync<NB_PV, 256>();
#pragma unroll
    for (int i = 0; i < 7; ++i) ld_rlx4(in[0][i], src[i] + 2 * BOX * i);
    wg_fence();
    turn_wait(turn);
#pragma unroll
    for (int s = 0; s < 5; ++s) {
      wgmma_n80(acc, o[s], dw + (wo_off(0) + 1024 * s >> 4), s);
      if (s == PASS0) turn_pass(pass);
    }
    wg_commit();
    TSTAMP(12);
#pragma unroll
    for (int s = 0; s < 5; ++s) {
      uint32_t (&cur)[7][4] = in[s % 3];
      if (s == 0) mbar_wait(bar + 8 * B_WO1, 0);
      sched_fence(P.zero);
      if (retry<1>(stale<7, 0>(cur, ep), budget)) {
#pragma unroll 1
        do {
#pragma unroll
          for (int i = 0; i < 7; ++i) ld_rlx4(cur[i], src[i] + (2 * BOX * i + 256 * s));
        } while (retry<1>(stale<7, 0>(cur, ep), budget));
      }
      TSTAMP(13 + s);
      if (s < 4) {
        if (s > 1) asm volatile("wgmma.wait_group.sync.aligned 1;" ::: "memory");
#pragma unroll
        for (int i = 0; i < 7; ++i) ld_rlx4(in[(s + 1) % 3][i], src[i] + (2 * BOX * i + 256 * (s + 1)));
      }
      if (s == 0) {
        st_rlx4(opub + 256 * 3, o[3]);
        st_rlx4(opub + 256 * 4, o[4]);
      }
      if (s == FGO_STEP && tid == 128) mbar_arrive(bar + 8 * B_GO);
      wg_fence();
      turn_wait(turn);
#pragma unroll
      for (int i = 0; i < 7; ++i) {
        wgmma_n80(acc, cur[i], dw + (wo_off(i + 1) + 1024 * s >> 4), 1);
        if (i == PASS_AT - 1 && (s < 4 || p == 0)) turn_pass(pass);
      }
      wg_commit();
    }
    mbar_wait(bar + 8 * B_TAB, 1);
    ld_row(ga, prow + R_GA);
    ldsm4(pb, lane & 1 ? prow + R_P : sb + OFF_PRM + R_ONE);
    ldsm4(pb + 4, lane & 1 ? prow + R_P + 64 : sb + OFF_PRM + R_ONE);
    ldsm2(pb + 8, lane & 1 ? prow + R_P + 128 : sb + OFF_PRM + R_ONE);
    uw = tag(lds1(sb + OFF_KEY + 64), ep);
    wg_wait();
  }
  TSTAMP(18);

  const uint32_t trow = 16 * rb + (lane & 15), xt = sb + (lane >> 4) * 16;
  {
#pragma unroll
    for (int k = 0; k < 20; ++k) xr[k >> 2][k & 3] = fma2(ga[k >> 1], pack2(acc[2 * k], acc[2 * k + 1]), xr[k >> 2][k & 3]);
    float s[4], qlo, qhi;
    row_stats(s, qlo, qhi, xr, pb, gq);
    if (t == gq >> 1) {
      st_rlx4(sdst, u32(s[0]), u32(s[1]), u32(qlo), uw);
      st_rlx4(sdst + 8, u32(s[2]), u32(s[3]), u32(qhi), uw);
    }
    sched_fence(P.zero);
    TSTAMP(19);
#pragma unroll
    for (int s5 = 0; s5 < 5; ++s5) stsm4(xt + trow * 176 + (OFF_X2 + 32 * s5), xr[s5]);
    uint32_t c1[10], sv[10], gb[10], m[4][4];
    ld_row(c1, prow + R_C1);
    ld_row(sv, prow + R_SB);
    ld_row(gb, prow + R_GB);
    wait_until(clock32() + ST2_GAP);
    gather_lazy<4, 2 * BOX, 4 * BOX, 3>(m, at<16>(P.sc + M_ST2, (16 * j + rank + 8 * (lane & 1)) * BOX + 16 * rb + (lane >> 1)), ep, budget);
    TSTAMP(20);
#pragma unroll
    for (int e = 0; e < 4; ++e) {
      s[e] = (f32(m[0][e]) + f32(m[1][e])) + (f32(m[2][e]) + f32(m[3][e]));
      s[e] += shx(s[e], 1);
    }
    float mean, rstd;
    const uint32_t nw = norm_word(s[0], s[2], mean, rstd), u = u32(rstd * fmaf(-mean, s[3], s[1]));
    const uint32_t key = ((u ^ ((uint32_t)((int)u >> 31) | 0x80000000u)) | 2047u) ^ (256 * j + 32 * rb + (lane & 30) + rank);
    if (key == __reduce_max_sync(0xFFFFFFFFu, key)) sts2(sb + OFF_KEY + 8 * rb, key, nw);
    bar_arrive<NB_KEY, 288>();
    TSTAMP(21);
    const uint32_t n0 = __shfl_sync(0xFFFFFFFFu, nw, 2 * gq), n1 = __shfl_sync(0xFFFFFFFFu, nw, 2 * gq + 16);
    nrm[0] = dup_hi(n0); nrm[1] = dup_hi(n1); nrm[2] = dup_lo(n0); nrm[3] = dup_lo(n1);
#pragma unroll
    for (int k = 0; k < 20; ++k) {
      uint32_t& x = xr[k >> 2][k & 3];
      x = fma2(gb[k >> 1], fma2(fma2(x, nrm[k & 1], nrm[2 + (k & 1)]), c1[k >> 1], sv[k >> 1]), x);
    }
    bar_sync<NB_PUB, 288>();
  }
  TSTAMP(22);

  if (p == 0 && b < N_FFN) {
    uint32_t wf[20][4], m[6][4];
    mbar_wait(bar + 8 * B_FFN, 1);
#pragma unroll
    for (int i = 0; i < 20; ++i)
      ldsm4t(wf[i], sb + OFF_FFN + (lane & 8) * 2560 + (80 * wq + 8 * (lane >> 4) + (lane & 7)) * 64 + (((i & 3) ^ ((lane >> 1) & 3)) << 4) + 1024 * (i >> 2));
    TSTAMP(23);
    const uint32_t far = map_to_cta(sb, 0), dst = far + OFF_ACT + (4 * rank + wq) * 128 + gq * 16, step = map_to_cta(sb, 1) - far;
    gather_lazy<6, 64 * BOX, 8, 0>(m, at<16>(P.sc + M_CAND, (8 * (gq & 6) + 8 * rank + 2 * wq) * BOX + (lane & 7)), ep, budget);
    TSTAMP(24);
    const bool second = m[5][2] > m[4][2];
    const uint32_t wtok = ~__reduce_max_sync(0xFFFFFFFFu, max(m[4][2], m[5][2]));
    float f[4][4];
#pragma unroll
    for (int s = 0; s < 5; ++s) {
      const uint32_t b0 = second ? m[(s & 6) + 1][2 * (s & 1)] : m[s & 6][2 * (s & 1)], b1 = second ? m[(s & 6) + 1][2 * (s & 1) + 1] : m[s & 6][2 * (s & 1) + 1];
#pragma unroll
      for (int mt = 0; mt < 4; ++mt) mma16(f[mt], wf[4 * s + mt], b0, b1, s ? f[mt] : z4);
    }
    if (t == ((wtok >> 8) & 3)) {
      const bool e = wtok & 1;
#pragma unroll
      for (int r = 0; r < 2; ++r)
        asm volatile("st.async.weak.shared::cluster.mbarrier::complete_tx::bytes.v4.f32 [%0], {%1, %2, %3, %4}, [%5];"
                     ::"r"(dst + r * step), "f"(e ? f[2 * r][1] : f[2 * r][0]), "f"(e ? f[2 * r][3] : f[2 * r][2]),
                       "f"(e ? f[2 * r + 1][1] : f[2 * r + 1][0]), "f"(e ? f[2 * r + 1][3] : f[2 * r + 1][2]), "r"(far + r * step + (OFF_BAR + 8 * B_ACT)) : "memory");
    }
    __syncwarp();
    if (warp == 0) {
      sts1(sb + OFF_KEY + 80, ~wtok);
      if (b < 80) bar_arrive<NB_WIN, 64>();
    }
    TSTAMP(25);
  }
#pragma unroll
  for (int s5 = 0; s5 < 5; ++s5) stsm4(xt + trow * 160 + (OFF_OUT + 32 * s5), xr[s5]);
  asm volatile("fence.proxy.async.shared::cta;" ::: "memory");
  asm volatile("bar.arrive %0, 160;" ::"r"(turn + (NB_OUT - NB_TURN)) : "memory");
  if (p == 1 && b < N_FFN) {
    const uint32_t kr = ((lane & 7) >> 1) + 4 * (lane >> 4) + 8 * (lane & 1);
    uint32_t wd[10][4];
    mbar_wait(bar + 8 * B_XS, 0);
#pragma unroll
    for (int i = 0; i < 10; ++i) ldsm4t(wd[i], sb + OFF_FFN + 40960 + kr * 128 + (((2 * wq + ((lane >> 3) & 1)) ^ (kr & 7)) << 4) + 2048 * i);
    TSTAMP(23);
    uint4* const ydst = at<16>(P.sc + M_YP, ((b & ~3) + wq) * BOX + 4 * (gq & 6) + 2 * (b & 3) + (gq & 1));
    mbar_wait(bar + 8 * B_ACT, 1);
    TSTAMP(24);
    float v[8];
#pragma unroll
    for (int i = 0; i < 8; ++i) v[i] = f32(lds1(sb + OFF_ACT + 128 * i + 4 * lane));
    const float gu = bf_round(((v[0] + v[1]) + (v[2] + v[3])) + ((v[4] + v[5]) + (v[6] + v[7])));
    const float a = bf_round(gu * sigmoid(gu)) * shx(gu, 1);
    const uint32_t aw = pack2(a, shx(a, 2));
    const uint32_t b0 = __shfl_sync(0xFFFFFFFFu, aw, 4 * t), b1 = __shfl_sync(0xFFFFFFFFu, aw, 4 * t + 16);
    const bool odd = gq & 1;
    float y[5][4];
#pragma unroll
    for (int q = 0; q < 5; ++q) mma16(y[q], wd[2 * q], odd ? 0u : b0, odd ? 0u : b1, z4);
#pragma unroll
    for (int q = 0; q < 5; ++q) mma16(y[q], wd[2 * q + 1], odd ? b0 : 0u, odd ? b1 : 0u, y[q]);
    uint32_t w[4];
#pragma unroll
    for (int e = 0; e < 4; ++e) w[e] = u32(t & 2 ? (t & 1 ? y[3][e] : y[2][e]) : (t & 1 ? y[1][e] : y[0][e]));
    st_rlx4(ydst + 32 * t, tag(w[0], ep), w[1], w[2], w[3]);
    if (t == 0) st_rlx4(ydst + 128, tag(u32(y[4][0]), ep), u32(y[4][1]), u32(y[4][2]), u32(y[4][3]));
    __syncwarp();
    if (warp == 4 && b < 80) bar_arrive<NB_YP, 64>();
    TSTAMP(25);
  }
}

__global__ void __cluster_dims__(2, 1, 1) __launch_bounds__(384, 1) fused_block_kernel(const __grid_constant__ Params P) {
  extern __shared__ __align__(1024) uint8_t sm[];
  const uint32_t sb = (uint32_t)__cvta_generic_to_shared(sm), t0 = clock32();
  const int tid = threadIdx.x, lane = tid & 31;
  uint32_t key = blockIdx.x;
  asm("mov.u32 %0, %%smid;" : "=r"(key));
  const __nv_bfloat16* wmod = (&P.wmod)[tid >> 9];
  asm volatile("" : "+l"(wmod));
  const int warp = __shfl_sync(0xFFFFFFFFu, tid >> 5, 0), c = key >> 1, rank = blockIdx.x & 1;
  const uint32_t bar = sb + OFF_BAR;
  const auto role = [&]() {
    const int q7 = ((c - 32) * 37) >> 8;
    return 2 * pick(c < 32, 8 * (c & 7) + (c >> 3), pick(c < 60, 8 * c - 55 * q7 - 244, c - 58)) + rank;
  };
  const bool spare = BY_SM && (c >> 1) == 30;
  int budget = SPIN_LIMIT, b;
  uint32_t e0 = 0;
  if (warp == 11) {
    if (elect_one()) {
#pragma unroll
      for (int i = 0; i < 12; ++i) mbar_init(bar + 8 * i, i == B_TAB ? 96 : i == B_HALO ? 8 : (i >> 2) == 1 ? 16 : 1);
      asm volatile("fence.mbarrier_init.release.cluster;" ::: "memory");
    }
    __syncwarp();
    asm volatile("barrier.cluster.arrive.relaxed.aligned;" ::: "memory");
    b = role();
    if (spare) {
      wait_until(t0 + 4000);
      return;
    }
    TSTAMP(27);
    const int g = (b >> 1) & 7;
    if (elect_one()) {
      mbar_expect_tx(bar + 8 * B_FULL, STAGE);
      tma2(sb, &P.xa, bar + 8 * B_FULL, 640 * rank, 128 * (b >> 4));
    }
    asm volatile("barrier.cluster.wait.aligned;" ::: "memory");
    if (elect_one()) {
      tma3_both(sb + STAGE_A + rank * (STAGE_B0 / 2), &P.w0, bar + 8 * B_FULL, 80 * g, 32 * rank, 0);
      tma3_both(sb + STAGE_A + STAGE_B0 + rank * (STAGE_B1 / 2), &P.w1, bar + 8 * B_FULL, 80 * g + 64, 32 * rank, 0);
    }
    TSTAMP(28);
    st_rlx1(at<4>(P.sc + M_ST1, b * (4 * BOX) + lane), 0u);
    wait_until(t0 + XS_AT);
    if (elect_one()) {
      mbar_expect_tx(bar + 8 * B_XS, 20480);
      bulk_load(sb + OFF_XS, P.x + b * 10240, 20480, bar + 8 * B_XS);
    }
  } else {
    asm volatile("barrier.cluster.arrive.relaxed.aligned;" ::: "memory");
    const int u = (c & 48) + 2 * (c & 7) + ((c >> 3) & 1) - (c & 32 ? c & 7 : 0), kb = 2 * u + rank;
    const bool gemv = warp < 10 && c < 40;
    uint32_t cv = 0;
    if (gemv) {
      const __nv_bfloat16* src = at<16>(wmod, (320 * rank + (tid >> 2)) * 480 + 4 * u + (tid & 3));
      const uint32_t dst = sb + 3 * STAGE + 16 * (tid ^ ((tid >> 3) & 3));
#pragma unroll
      for (int i = 0; i < 4; ++i)
        asm volatile("cp.async.cg.shared.global.L2::128B [%0], [%1], 16;" ::"r"(dst + 5120 * i), "l"(src + i * 80 * 3840) : "memory");
    } else if (warp == 10 && elect_one()) {
      asm volatile("prefetch.tensormap [%0];" ::"l"(&P.xa) : "memory");
      asm volatile("prefetch.tensormap [%0];" ::"l"(&P.w0) : "memory");
      asm volatile("prefetch.tensormap [%0];" ::"l"(&P.w1) : "memory");
    }
    TSTAMP(26);
    asm volatile("barrier.cluster.wait.aligned;" ::: "memory");
    if (spare) return;
    if (gemv) asm volatile("ld.global.nc.u16 %0, [%1];" : "=r"(cv) : "l"(at<2>(P.c, 320 * rank + 10 * (tid & 24) + ((tid >> 2) & ~7) + (tid & 7))));
    b = role();
    uint4* const box = P.sc + b * BOX;
    e0 = ld_rlx1(at<4>(box + M_EPOCH, lane));
    if (warp == 10) {
      uint4* const dst = at<16>(P.sc, kb * BOX + lane);
      if (c < 40) st_rlx4(dst, 0u, 0u, 0u, 0u);
      if (lane == 0) mbar_expect_tx(bar + 8 * B_GO, c < 40 ? 1280 : 0);
      TALIGN(0);
      if (c < 40) {
        const uint32_t ep = next_epoch(e0);
        mbar_wait(bar + 8 * B_GO, 0);
        TSTAMP(1);
        float v[10];
#pragma unroll
        for (int i = 0; i < 10; ++i) v[i] = f32(lds1(sb + OFF_RED + 128 * i + 4 * lane));
        float s = ((v[0] + v[1]) + (v[2] + v[3])) + ((v[4] + v[5]) + (v[6] + v[7])) + (v[8] + v[9]);
        s += shx(s, 16);
        const uint32_t w = fma2(pack2(s, shx(s, 1)), 0x3F803F80u, kb < 40 ? 0u : 0x3F803F80u);
        st_rlx4(dst, __shfl_sync(0xFFFFFFFFu, w, 2 * (lane & 3)), __shfl_sync(0xFFFFFFFFu, w, 2 * (lane & 3) + 8), ep, ep);
        TSTAMP(2);
      }
    } else if (gemv) {
      const float x = bf_lo(cv), s = x * sigmoid(x);
      const uint32_t sw = pack2(s, shx(s, 1));
      uint32_t bw[4], a[4][4];
#pragma unroll
      for (int i = 0; i < 4; ++i) bw[i] = __shfl_sync(0xFFFFFFFFu, sw, 8 * i + 2 * (lane & 3));
      const uint32_t far = map_to_cta(sb, (lane >> 1) & 1), dst = far + OFF_RED + 128 * warp + 64 * rank + 32 * (lane & 1) + (lane & 28);
      const uint32_t la = sb + 3 * STAGE + 512 * warp + (lane >> 4) * 5120 + (lane & 7) * 64 + ((((lane >> 3) & 1) ^ ((lane >> 1) & 3)) << 4);
      sched_fence(P.zero);
      asm volatile("cp.async.wait_all;" ::: "memory");
      __syncwarp();
      TSTAMP(28);
#pragma unroll
      for (int i = 0; i < 4; ++i) ldsm4t(a[i], (la ^ (32 * (i & 1))) + (i >> 1) * 10240);
      float d[2][4];
      const float z4[4] = {0.f, 0.f, 0.f, 0.f};
#pragma unroll
      for (int i = 0; i < 4; ++i) mma16(d[i & 1], a[i], bw[i & 2], bw[(i & 2) + 1], i < 2 ? z4 : d[i & 1]);
      const float v = lane & 2 ? (lane & 1 ? d[1][2] : d[1][0]) : (lane & 1 ? d[0][2] : d[0][0]);
      asm volatile("st.async.weak.shared::cluster.mbarrier::complete_tx::bytes.f32 [%0], %1, [%2];" ::"r"(dst), "f"(v), "r"(far + OFF_BAR + 8 * B_GO) : "memory");
      TSTAMP(1);
    }
  }
  if (warp >= 8) {
    asm volatile("setmaxnreg.dec.sync.aligned.u32 56;");
    if (warp == 11) {
      wait_until(t0 + S_GAP);
      run_producer(P, sm, sb, b, t0);
    } else {
      run_helper(P, sm, sb, b, warp - 8, next_epoch(e0), budget, t0 + POLL_AT);
    }
    TDUMP();
  } else {
    run_consumer(P, sm, sb, b, warp, next_epoch(e0), budget);
    TDUMP();
  }
}

typedef CUresult (*EncodeFn)(CUtensorMap*, CUtensorMapDataType, cuuint32_t, void*, const cuuint64_t*, const cuuint64_t*, const cuuint32_t*,
                             const cuuint32_t*, CUtensorMapInterleave, CUtensorMapSwizzle, CUtensorMapL2promotion, CUtensorMapFloatOOBfill);

void encode(EncodeFn fn, CUtensorMap* m, const void* base, int rank, const cuuint64_t* dims, const cuuint64_t* strides, const cuuint32_t* box,
            CUtensorMapSwizzle sw) {
  const cuuint32_t es[3] = {1, 1, 1};
  fn(m, CU_TENSOR_MAP_DATA_TYPE_BFLOAT16, rank, const_cast<void*>(base), dims, strides, box, es, CU_TENSOR_MAP_INTERLEAVE_NONE, sw,
     CU_TENSOR_MAP_L2_PROMOTION_L2_128B, CU_TENSOR_MAP_FLOAT_OOB_FILL_NONE);
}

}

extern "C" void kernel_launch(void* const* d_in, const int* in_sizes, int n_in, void* d_out, int out_size) {
  (void)in_sizes; (void)n_in; (void)out_size;
  static EncodeFn fn = nullptr;
  static void* scratch = nullptr;
  if (!fn) {
    void* f = nullptr;
    cudaDriverEntryPointQueryResult q;
    cudaGetDriverEntryPoint("cuTensorMapEncodeTiled", &f, cudaEnableDefault, &q);
    fn = (EncodeFn)f;
    cudaFuncSetAttribute(fused_block_kernel, cudaFuncAttributeMaxDynamicSharedMemorySize, SMEM_BYTES);
    cudaGetSymbolAddress(&scratch, g_scratch);
  }
  Params P;
  P.sc = (uint4*)scratch;
  P.zero = 0;
  const cuuint64_t xd[2] = {1280, 1024}, xs[1] = {2560};
  const cuuint32_t xb[2] = {64, 128};
  encode(fn, &P.xa, d_in[0], 2, xd, xs, xb, CU_TENSOR_MAP_SWIZZLE_128B);
  const cuuint32_t ob[2] = {80, 16};
  encode(fn, &P.om, d_out, 2, xd, xs, ob, CU_TENSOR_MAP_SWIZZLE_NONE);
  const cuuint64_t wd3[3] = {640, 640, 3}, ws3[2] = {3840, 1280};
  const cuuint32_t w0b[3] = {64, 32, 3}, w1b[3] = {16, 32, 3};
  encode(fn, &P.w0, d_in[1], 3, wd3, ws3, w0b, CU_TENSOR_MAP_SWIZZLE_128B);
  encode(fn, &P.w1, d_in[1], 3, wd3, ws3, w1b, CU_TENSOR_MAP_SWIZZLE_32B);
  const cuuint64_t md[2] = {3840, 640}, ms[1] = {7680};
  const cuuint32_t mb[2] = {80, 160};
  encode(fn, &P.wm, d_in[9], 2, md, ms, mb, CU_TENSOR_MAP_SWIZZLE_NONE);
  const cuuint64_t od3[3] = {608, 640, 2}, os3[2] = {1280, 64}, od2[2] = {640, 640}, os2[1] = {1280};
  const cuuint32_t oab[3] = {32, 80, 2}, obb[2] = {16, 80};
  encode(fn, &P.woa, d_in[2], 3, od3, os3, oab, CU_TENSOR_MAP_SWIZZLE_64B);
  encode(fn, &P.wob, d_in[2], 2, od2, os2, obb, CU_TENSOR_MAP_SWIZZLE_64B);
  const cuuint64_t gd[3] = {1728, 160, 4}, gs[2] = {3456, 160 * 3456}, dd[3] = {64, 1728, 10}, ds[2] = {1280, 128};
  const cuuint32_t gb[3] = {32, 160, 1}, db[3] = {64, 16, 5};
  encode(fn, &P.wg, d_in[5], 3, gd, gs, gb, CU_TENSOR_MAP_SWIZZLE_64B);
  encode(fn, &P.wu, d_in[6], 3, gd, gs, gb, CU_TENSOR_MAP_SWIZZLE_64B);
  encode(fn, &P.wd, d_in[7], 3, dd, ds, db, CU_TENSOR_MAP_SWIZZLE_128B);
  P.x = (const __nv_bfloat16*)d_in[0];
  P.wqkv = (const __nv_bfloat16*)d_in[1];
  P.wr = (const __nv_bfloat16*)d_in[4];
  P.wo = (const __nv_bfloat16*)d_in[2];
  P.wgate = (const __nv_bfloat16*)d_in[5];
  P.wup = (const __nv_bfloat16*)d_in[6];
  P.wdown = (const __nv_bfloat16*)d_in[7];
  P.c = (const __nv_bfloat16*)d_in[8];
  P.wmod = (const __nv_bfloat16*)d_in[9];
  P.out = (__nv_bfloat16*)d_out;
  fused_block_kernel<<<BY_SM ? 132 : 128, 384, SMEM_BYTES>>>(P);
}
```

```cpp
#include <cuda_runtime.h>
#include <cuda.h>
#include <cuda_bf16.h>
#include <stdint.h>

namespace {

constexpr int STAGE_A = 16384, STAGE_B0 = 24576, STAGE_B1 = 6144, STAGE = STAGE_A + STAGE_B0 + STAGE_B1;
constexpr int WO = 15360;
constexpr int OFF_FFN = 4 * WO, OFF_LM = 2 * STAGE, OFF_X2 = 4 * STAGE, OFF_OUT = 0;
constexpr int OFF_H = 4 * STAGE, OFF_L = OFF_H + 9 * 2560, OFF_XS = OFF_H, OFF_RED = OFF_L, OFF_SINK = OFF_L + 10240;
constexpr int OFF_C1 = 225280, OFF_ACT = OFF_C1, OFF_PRM = OFF_C1 + 2560, OFF_SILU = OFF_PRM + 1600;
constexpr int OFF_KEY = OFF_SILU + 320, OFF_BAR = OFF_KEY + 128, OFF_TIME = OFF_BAR + 256, SMEM_BYTES = OFF_TIME + 1536;
static_assert(OFF_H % 512 == 0, "lane bits of the halo address");
static_assert(SMEM_BYTES <= 232448 && OFF_BAR % 64 == 0, "smem");
enum { R_GA = 0, R_SB = 160, R_C1 = 320, R_GB = 480, R_FIN = 640, R_P = 800 + R_C1, R_ONE = 704 };

enum { B_FULL = 0, B_EMPTY = 4, B_HALO = 8, B_TAB = 9, B_GO = 10, B_XS = 11, B_ACT = B_FULL, B_FFN = B_FULL + 1, B_WO0 = B_FULL + 2, B_WO1 = B_FULL + 3 };
enum { NB_PV = 1, NB_TURN = 2, NB_KEY = 4, NB_REDO = 5, NB_HELP = 6, NB_HALO = 7, NB_PUB = 8, NB_GO = 9, NB_LM = 10, NB_OUT = 11, NB_WIN = 13, NB_YP = 14 };

enum { M_EARLY = 0, M_ST1 = 32, M_EPOCH = 40, M_HALO = 48, M_ST2 = 208, M_CAND = 336, M_LATE = 368, M_YP = 400, M_O = 560, BOX = 1840 };
__device__ uint4 g_scratch[128 * BOX];

constexpr int N_FFN = 108;
#define BY_SM 1
#define HI_FIRST 0
#define HALO_FENCE 1
#define AHEAD 1
#define PUB34 2
#define FORCE_REDO 0
#define FFN_EARLY 0
#define DOWN_GAP 1900
#define PRM_FIRST 1
#define NAP 20
#define XS_AT 900
#define S_GAP 1300
#define POLL_AT 4000
#define WPF_AT 4500
#define LMPF_AT 4
#define TOUCH_AT 1000
#define TOUCH_GAP 1100
#define HALO_GAP 400
#define LATE_GAP 1100
#define FGO_STEP 4
#define FFN_GAP 0
#define ST2_GAP 0
#define OUT_AT 250
#define OUT_GAP 80
#define YP_GAP 250
#define PASS1 5
#define PASS0 2
#define PASS_AT 3
constexpr int SPIN_LIMIT = 1 << 16;

struct Params {
  const __nv_bfloat16 *wmod, *c, *x;
  uint4* sc;
  uint32_t zero;
  const __nv_bfloat16 *wqkv, *wr, *wo, *wgate, *wup, *wdown;
  __nv_bfloat16* out;
  CUtensorMap xa, w0, w1, wm, woa, wob, wg, wu, wd, om;
};

__device__ __forceinline__ uint32_t clock32() {
  uint32_t c;
  asm volatile("mov.u32 %0, %%clock;" : "=r"(c));
  return c;
}
#define TSTAMP(i) do { } while (0)
#define TDUMP() do { } while (0)
#define TALIGN(k) do { } while (0)

__device__ __forceinline__ void mbar_init(uint32_t b, uint32_t c) { asm volatile("mbarrier.init.shared::cta.b64 [%0], %1;" ::"r"(b), "r"(c) : "memory"); }
__device__ __forceinline__ void mbar_expect_tx(uint32_t b, uint32_t n) { asm volatile("mbarrier.arrive.expect_tx.shared::cta.b64 _, [%0], %1;" ::"r"(b), "r"(n) : "memory"); }
__device__ __forceinline__ void mbar_arrive(uint32_t b) { asm volatile("mbarrier.arrive.shared::cta.b64 _, [%0];" ::"r"(b) : "memory"); }
__device__ __forceinline__ uint32_t map_to_cta(uint32_t a, uint32_t rank) {
  uint32_t r;
  asm("mapa.shared::cluster.u32 %0, %1, %2;" : "=r"(r) : "r"(a), "r"(rank));
  return r;
}
__device__ __forceinline__ void mbar_arrive_cluster(uint32_t b) { asm volatile("mbarrier.arrive.shared::cluster.b64 _, [%0];" ::"r"(b) : "memory"); }
__device__ __forceinline__ void mbar_wait(uint32_t b, uint32_t ph) {
  asm volatile("{.reg .pred p;\n"
               "RETRY: mbarrier.try_wait.parity.shared::cta.b64 p, [%0], %1;\n"
               "@!p bra RETRY;}" ::"r"(b), "r"(ph) : "memory");
}
__device__ __forceinline__ bool elect_one() {
  uint32_t r;
  asm volatile("{.reg .pred p; elect.sync _|p, 0xFFFFFFFF; selp.u32 %0, 1, 0, p;}" : "=r"(r));
  return r;
}
template <int ID, int N> __device__ __forceinline__ void bar_sync() { asm volatile("bar.sync %0, %1;" ::"n"(ID), "n"(N) : "memory"); }
template <int ID, int N> __device__ __forceinline__ void bar_arrive() { asm volatile("bar.arrive %0, %1;" ::"n"(ID), "n"(N) : "memory"); }
__device__ __forceinline__ void turn_wait(uint32_t id) { asm volatile("bar.sync %0, 256;" ::"r"(id) : "memory"); }
__device__ __forceinline__ void turn_pass(uint32_t id) { asm volatile("bar.arrive %0, 256;" ::"r"(id) : "memory"); }
__device__ __forceinline__ void tma2(uint32_t dst, const CUtensorMap* m, uint32_t bar, int c0, int c1) {
  asm volatile("cp.async.bulk.tensor.2d.shared::cluster.global.mbarrier::complete_tx::bytes [%0], [%1, {%3, %4}], [%2];" ::"r"(dst), "l"(m), "r"(bar), "r"(c0), "r"(c1) : "memory");
}
__device__ __forceinline__ void tma3(uint32_t dst, const CUtensorMap* m, uint32_t bar, int c0, int c1, int c2) {
  asm volatile("cp.async.bulk.tensor.3d.shared::cluster.global.mbarrier::complete_tx::bytes [%0], [%1, {%3, %4, %5}], [%2];" ::"r"(dst), "l"(m), "r"(bar), "r"(c0), "r"(c1), "r"(c2) : "memory");
}
__device__ __forceinline__ void tma2_both(uint32_t dst, const CUtensorMap* m, uint32_t bar, int c0, int c1) {
  asm volatile("cp.async.bulk.tensor.2d.shared::cluster.global.mbarrier::complete_tx::bytes.multicast::cluster [%0], [%1, {%3, %4}], [%2], %5;"
               ::"r"(dst), "l"(m), "r"(bar), "r"(c0), "r"(c1), "h"((uint16_t)3) : "memory");
}
__device__ __forceinline__ void tma3_both(uint32_t dst, const CUtensorMap* m, uint32_t bar, int c0, int c1, int c2) {
  asm volatile("cp.async.bulk.tensor.3d.shared::cluster.global.mbarrier::complete_tx::bytes.multicast::cluster [%0], [%1, {%3, %4, %5}], [%2], %6;"
               ::"r"(dst), "l"(m), "r"(bar), "r"(c0), "r"(c1), "r"(c2), "h"((uint16_t)3) : "memory");
}
__device__ __forceinline__ void bulk_prefetch(const void* src, uint32_t bytes) {
  asm volatile("cp.async.bulk.prefetch.L2.global [%0], %1;" ::"l"(src), "r"(bytes) : "memory");
}
__device__ __forceinline__ void wg_fence() { asm volatile("wgmma.fence.sync.aligned;" ::: "memory"); }
__device__ __forceinline__ void wg_commit() { asm volatile("wgmma.commit_group.sync.aligned;" ::: "memory"); }
__device__ __forceinline__ void wg_wait() { asm volatile("wgmma.wait_group.sync.aligned 0;" ::: "memory"); }
__device__ __forceinline__ uint64_t make_desc(uint32_t addr, uint32_t lbo, uint32_t sbo, uint32_t mode) {
  return (uint64_t)((addr & 0x3FFFF) >> 4) | ((uint64_t)(lbo >> 4) << 16) | ((uint64_t)(sbo >> 4) << 32) | ((uint64_t)mode << 62);
}
__device__ __forceinline__ void ldsm4(uint32_t& r0, uint32_t& r1, uint32_t& r2, uint32_t& r3, uint32_t a) {
  asm volatile("ldmatrix.sync.aligned.m8n8.x4.shared.b16 {%0, %1, %2, %3}, [%4];" : "=r"(r0), "=r"(r1), "=r"(r2), "=r"(r3) : "r"(a) : "memory");
}
__device__ __forceinline__ void ldsm4(uint32_t* r, uint32_t a) { ldsm4(r[0], r[1], r[2], r[3], a); }
__device__ __forceinline__ void ldsm2(uint32_t* r, uint32_t a) {
  asm volatile("ldmatrix.sync.aligned.m8n8.x2.shared.b16 {%0, %1}, [%2];" : "=r"(r[0]), "=r"(r[1]) : "r"(a) : "memory");
}
__device__ __forceinline__ void ldsm4t(uint32_t* r, uint32_t a) {
  asm volatile("ldmatrix.sync.aligned.m8n8.x4.trans.shared.b16 {%0, %1, %2, %3}, [%4];" : "=r"(r[0]), "=r"(r[1]), "=r"(r[2]), "=r"(r[3]) : "r"(a) : "memory");
}
__device__ __forceinline__ void ldsm2t(uint32_t* r, uint32_t a) {
  asm volatile("ldmatrix.sync.aligned.m8n8.x2.trans.shared.b16 {%0, %1}, [%2];" : "=r"(r[0]), "=r"(r[1]) : "r"(a) : "memory");
}
__device__ __forceinline__ void ld_row(uint32_t (&r)[10], uint32_t a) {
  ldsm4(r, a);
  ldsm4(r + 4, a + 64);
  ldsm2(r + 8, a + 128);
}
__device__ __forceinline__ void stsm4(uint32_t a, const uint32_t* r) {
  asm volatile("stmatrix.sync.aligned.m8n8.x4.shared.b16 [%0], {%1, %2, %3, %4};" ::"r"(a), "r"(r[0]), "r"(r[1]), "r"(r[2]), "r"(r[3]) : "memory");
}
__device__ __forceinline__ void stsm2(uint32_t a, const uint32_t* r) {
  asm volatile("stmatrix.sync.aligned.m8n8.x2.shared.b16 [%0], {%1, %2};" ::"r"(a), "r"(r[0]), "r"(r[1]) : "memory");
}
__device__ __forceinline__ void lds4(uint32_t* r, uint32_t a) {
  asm volatile("ld.shared.v4.u32 {%0, %1, %2, %3}, [%4];" : "=r"(r[0]), "=r"(r[1]), "=r"(r[2]), "=r"(r[3]) : "r"(a) : "memory");
}
__device__ __forceinline__ uint32_t lds1(uint32_t a) {
  uint32_t v;
  asm volatile("ld.shared.u32 %0, [%1];" : "=r"(v) : "r"(a) : "memory");
  return v;
}
__device__ __forceinline__ void sts1(uint32_t a, uint32_t v) { asm volatile("st.shared.u32 [%0], %1;" ::"r"(a), "r"(v) : "memory"); }
__device__ __forceinline__ void sts2(uint32_t a, uint32_t v0, uint32_t v1) { asm volatile("st.shared.v2.u32 [%0], {%1, %2};" ::"r"(a), "r"(v0), "r"(v1) : "memory"); }
__device__ __forceinline__ void mma16(float (&d)[4], uint32_t a0, uint32_t a1, uint32_t a2, uint32_t a3, uint32_t b0, uint32_t b1, const float* c) {
  asm volatile("mma.sync.aligned.m16n8k16.row.col.f32.bf16.bf16.f32 {%0, %1, %2, %3}, {%4, %5, %6, %7}, {%8, %9}, {%10, %11, %12, %13};"
               : "=f"(d[0]), "=f"(d[1]), "=f"(d[2]), "=f"(d[3])
               : "r"(a0), "r"(a1), "r"(a2), "r"(a3), "r"(b0), "r"(b1), "f"(c[0]), "f"(c[1]), "f"(c[2]), "f"(c[3]));
}
__device__ __forceinline__ void mma16(float (&d)[4], const uint32_t* a, uint32_t b0, uint32_t b1, const float* c) { mma16(d, a[0], a[1], a[2], a[3], b0, b1, c); }
__device__ __forceinline__ void mma8(float (&d)[4], uint32_t a0, uint32_t a1, uint32_t b0, const float* c) {
  asm volatile("mma.sync.aligned.m16n8k8.row.col.f32.bf16.bf16.f32 {%0, %1, %2, %3}, {%4, %5}, {%6}, {%7, %8, %9, %10};"
               : "=f"(d[0]), "=f"(d[1]), "=f"(d[2]), "=f"(d[3]) : "r"(a0), "r"(a1), "r"(b0), "f"(c[0]), "f"(c[1]), "f"(c[2]), "f"(c[3]));
}
__device__ __forceinline__ uint32_t pack2(float lo, float hi) {
  uint32_t r;
  asm volatile("cvt.rn.bf16x2.f32 %0, %1, %2;" : "=r"(r) : "f"(hi), "f"(lo));
  return r;
}
__device__ __forceinline__ float bf_lo(uint32_t w) { return __uint_as_float(w << 16); }
__device__ __forceinline__ float bf_hi(uint32_t w) { return __uint_as_float(w & 0xFFFF0000u); }
__device__ __forceinline__ float bf_round(float v) { return __uint_as_float(pack2(0.f, v)); }
__device__ __forceinline__ uint32_t fma2(uint32_t a, uint32_t b, uint32_t c) {
  uint32_t r;
  asm("fma.rn.bf16x2 %0, %1, %2, %3;" : "=r"(r) : "r"(a), "r"(b), "r"(c));
  return r;
}
__device__ __forceinline__ float ex2(float v) {
  float r;
  asm("ex2.approx.ftz.f32 %0, %1;" : "=f"(r) : "f"(v));
  return r;
}
__device__ __forceinline__ float rcp(float v) {
  float r;
  asm("rcp.approx.ftz.f32 %0, %1;" : "=f"(r) : "f"(v));
  return r;
}
__device__ __forceinline__ float rsq(float v) {
  float r;
  asm("rsqrt.approx.ftz.f32 %0, %1;" : "=f"(r) : "f"(v));
  return r;
}
__device__ __forceinline__ float sigmoid(float v) { return rcp(1.f + ex2(v * -1.4426950408889634f)); }
__device__ __forceinline__ float f32(uint32_t v) { return __uint_as_float(v); }
__device__ __forceinline__ uint32_t u32(float v) { return __float_as_uint(v); }
__device__ __forceinline__ void ld_rlx4(uint32_t* v, const void* p) {
  asm volatile("{.reg .b128 q; ld.relaxed.gpu.global.b128 q, [%4]; mov.b128 {%0, %1, %2, %3}, q;}" : "=r"(v[0]), "=r"(v[1]), "=r"(v[2]), "=r"(v[3]) : "l"(p) : "memory");
}
__device__ __forceinline__ void ld_rlx2(uint32_t* v, const void* p) {
  asm volatile("{.reg .b64 q; ld.relaxed.gpu.global.b64 q, [%2]; mov.b64 {%0, %1}, q;}" : "=r"(v[0]), "=r"(v[1]) : "l"(p) : "memory");
}
__device__ __forceinline__ uint32_t ld_rlx1(const void* p) {
  uint32_t v;
  asm volatile("ld.relaxed.gpu.global.u32 %0, [%1];" : "=r"(v) : "l"(p) : "memory");
  return v;
}
__device__ __forceinline__ void st_rlx4(void* p, uint32_t a, uint32_t b, uint32_t c, uint32_t d) {
  asm volatile("{.reg .b128 q; mov.b128 q, {%1, %2, %3, %4}; st.relaxed.gpu.global.b128 [%0], q;}" ::"l"(p), "r"(a), "r"(b), "r"(c), "r"(d) : "memory");
}
__device__ __forceinline__ void st_rlx4(void* p, const uint32_t* v) { st_rlx4(p, v[0], v[1], v[2], v[3]); }
__device__ __forceinline__ void st_rlx2(void* p, uint32_t a, uint32_t b) { asm volatile("{.reg .b64 q; mov.b64 q, {%1, %2}; st.relaxed.gpu.global.b64 [%0], q;}" ::"l"(p), "r"(a), "r"(b) : "memory"); }
__device__ __forceinline__ void st_rlx1(void* p, uint32_t v) { asm volatile("st.relaxed.gpu.global.u32 [%0], %1;" ::"l"(p), "r"(v) : "memory"); }
template <int LUT> __device__ __forceinline__ uint32_t lop3(uint32_t a, uint32_t b, uint32_t c) {
  uint32_t r;
  asm volatile("lop3.b32 %0, %1, %2, %3, %4;" : "=r"(r) : "r"(a), "r"(b), "r"(c), "n"(LUT));
  return r;
}
__device__ __forceinline__ uint32_t tag(uint32_t w, uint32_t ep) { return lop3<0xD8>(w, ep, 1u); }
__device__ __forceinline__ uint32_t neq2(uint32_t a, uint32_t b, uint32_t e) { return lop3<0x7E>(a, b, e); }
__device__ __forceinline__ uint32_t next_epoch(uint32_t e) {
  asm volatile("add.u32 %0, %0, 1;" : "+r"(e));
  return e;
}
__device__ __forceinline__ void sched_fence(uint32_t zero) {
  asm volatile("{.reg .pred p; setp.ne.u32 p, %0, 0;\nSPIN: pmevent 0; @p bra.uni SPIN;}" ::"r"(zero) : "memory");
}
__device__ __forceinline__ int pick(bool c, int a, int b) {
  int r;
  asm("{.reg .pred p; setp.ne.u32 p, %1, 0; selp.b32 %0, %2, %3, p;}" : "=r"(r) : "r"((uint32_t)c), "r"(a), "r"(b));
  return r;
}
__device__ __forceinline__ uint32_t keep(uint32_t v) { return __shfl_xor_sync(0xFFFFFFFFu, v, 2); }
__device__ __forceinline__ void wait_until(uint32_t t) {
  while ((int)(clock32() - t) < 0) {
    asm volatile("nanosleep.u32 %0;" ::"n"(NAP));
  }
}
__device__ __forceinline__ float shx(float v, int o) { return __shfl_xor_sync(0xFFFFFFFFu, v, o); }
template <int SCALE, class T> __device__ __forceinline__ T* at(T* base, uint32_t i) {
  T* r;
  asm volatile("mad.wide.u32 %0, %1, %2, %3;" : "=l"(r) : "r"(i), "n"(SCALE), "l"(base));
  return r;
}
template <uint32_t MASK> __device__ __forceinline__ bool retry(uint32_t bad, int& budget) {
  uint32_t r;
  asm volatile("{.reg .pred p, q; .reg .b32 t; add.s32 %1, %1, -1; setp.gt.s32 q, %1, 0; and.b32 t, %2, %3; setp.ne.and.u32 p, t, 0, q;\n"
               "vote.sync.any.pred p, p, 0xFFFFFFFF; selp.u32 %0, 1, 0, p;}" : "=r"(r), "+r"(budget) : "r"(bad), "n"(MASK));
  return r;
}
template <int N, int W> __device__ __forceinline__ uint32_t stale(const uint32_t (*v)[4], uint32_t ep) {
  uint32_t bad = neq2(v[0][W], v[N > 1][W], ep);
#pragma unroll
  for (int i = 2; i < N; i += 2) bad |= neq2(v[i][W], v[i + 1 < N ? i + 1 : i][W], ep);
  return bad;
}
__device__ __forceinline__ void ld_rlx4_stale(uint32_t* v, const void* p, uint32_t w, uint32_t ep) {
  asm volatile("{.reg .b128 q; .reg .pred p; .reg .b32 t; lop3.b32 t, %5, %6, 1, 0x28; setp.ne.u32 p, t, 0; mov.b128 q, {%0, %1, %2, %3};\n"
               "@p ld.relaxed.gpu.global.b128 q, [%4]; mov.b128 {%0, %1, %2, %3}, q;}"
               : "+r"(v[0]), "+r"(v[1]), "+r"(v[2]), "+r"(v[3]) : "l"(p), "r"(w), "r"(ep) : "memory");
}
template <int N, int S0, int S1, int W> __device__ __forceinline__ void gather_lazy(uint32_t (*v)[4], const uint4* p, uint32_t ep, int& budget, bool skip_last = false) {
#pragma unroll
  for (int i = 0; i < 4 * N; ++i) {
    if ((i & 3) == W) v[i >> 2][W] = N == 7 && i >= 24 && skip_last ? ep & 1u : ~ep;
    else if (N == 7 && i >= 24) v[6][i & 3] = 0;
    else asm volatile("" : "=r"(v[i >> 2][i & 3]));
  }
#pragma unroll 1
  do {
#pragma unroll
    for (int i = 0; i < N; ++i) ld_rlx4_stale(v[i], p + (i & 1) * S0 + (i >> 1) * S1, v[i][W], ep);
  } while (retry<1>(stale<N, W>(v, ep), budget));
}
template <int N, int STRIDE, int W> __device__ __forceinline__ void gather(uint32_t (*v)[4], const uint4* p, uint32_t ep, int& budget) {
#pragma unroll 1
  do {
#pragma unroll
    for (int i = 0; i < N; ++i) ld_rlx4(v[i], p + i * STRIDE);
  } while (retry<1>(stale<N, W>(v, ep), budget));
}
__device__ __forceinline__ void row_stats(float (&s)[4], float& qlo, float& qhi, const uint32_t (&x)[5][4], const uint32_t (&b)[10], int gq) {
  const float z[4] = {0.f, 0.f, 0.f, 0.f};
  float q[4][4];
#pragma unroll
  for (int i = 0; i < 5; ++i) {
    mma16(s, x[i], b[2 * i], b[2 * i + 1], i ? s : z);
#pragma unroll
    for (int e = 0; e < 4; ++e) mma8(q[e], x[i][e & 2], x[i][(e & 2) + 1], x[i][e], i ? q[e] : z);
  }
  const bool odd = gq & 1;
  qlo = (odd ? q[0][1] : q[0][0]) + (odd ? q[2][1] : q[2][0]);
  qhi = (odd ? q[1][3] : q[1][2]) + (odd ? q[3][3] : q[3][2]);
}
__device__ __forceinline__ uint32_t norm_word(float s, float q, float& mean, float& rstd) {
  mean = s * (1.f / 640.f);
  rstd = rsq(fmaxf(fmaf(q, 1.f / 640.f, -mean * mean), 0.f) + 1e-5f);
  return pack2(-mean * bf_round(rstd), rstd);
}
__device__ __forceinline__ uint32_t dup_lo(uint32_t w) { return __byte_perm(w, 0u, 0x1010); }
__device__ __forceinline__ uint32_t dup_hi(uint32_t w) { return __byte_perm(w, 0u, 0x3232); }

__device__ __forceinline__ void wgmma_n192(float (&d)[96], const uint32_t (&a)[4], uint64_t db, int add) {
  asm volatile("{.reg .pred p; setp.ne.b32 p, %101, 0; wgmma.mma_async.sync.aligned.m64n192k16.f32.bf16.bf16 "
    "{%0, %1, %2, %3, %4, %5, %6, %7, %8, %9, %10, %11, %12, %13, %14, %15, "
    "%16, %17, %18, %19, %20, %21, %22, %23, %24, %25, %26, %27, %28, %29, %30, %31, "
    "%32, %33, %34, %35, %36, %37, %38, %39, %40, %41, %42, %43, %44, %45, %46, %47, "
    "%48, %49, %50, %51, %52, %53, %54, %55, %56, %57, %58, %59, %60, %61, %62, %63, "
    "%64, %65, %66, %67, %68, %69, %70, %71, %72, %73, %74, %75, %76, %77, %78, %79, "
    "%80, %81, %82, %83, %84, %85, %86, %87, %88, %89, %90, %91, %92, %93, %94, %95}, "
    "{%96, %97, %98, %99}, %100, p, 1, 1, 1;}"
    : "+f"(d[0]), "+f"(d[1]), "+f"(d[2]), "+f"(d[3]), "+f"(d[4]), "+f"(d[5]), "+f"(d[6]), "+f"(d[7]),
      "+f"(d[8]), "+f"(d[9]), "+f"(d[10]), "+f"(d[11]), "+f"(d[12]), "+f"(d[13]), "+f"(d[14]), "+f"(d[15]),
      "+f"(d[16]), "+f"(d[17]), "+f"(d[18]), "+f"(d[19]), "+f"(d[20]), "+f"(d[21]), "+f"(d[22]), "+f"(d[23]),
      "+f"(d[24]), "+f"(d[25]), "+f"(d[26]), "+f"(d[27]), "+f"(d[28]), "+f"(d[29]), "+f"(d[30]), "+f"(d[31]),
      "+f"(d[32]), "+f"(d[33]), "+f"(d[34]), "+f"(d[35]), "+f"(d[36]), "+f"(d[37]), "+f"(d[38]), "+f"(d[39]),
      "+f"(d[40]), "+f"(d[41]), "+f"(d[42]), "+f"(d[43]), "+f"(d[44]), "+f"(d[45]), "+f"(d[46]), "+f"(d[47]),
      "+f"(d[48]), "+f"(d[49]), "+f"(d[50]), "+f"(d[51]), "+f"(d[52]), "+f"(d[53]), "+f"(d[54]), "+f"(d[55]),
      "+f"(d[56]), "+f"(d[57]), "+f"(d[58]), "+f"(d[59]), "+f"(d[60]), "+f"(d[61]), "+f"(d[62]), "+f"(d[63]),
      "+f"(d[64]), "+f"(d[65]), "+f"(d[66]), "+f"(d[67]), "+f"(d[68]), "+f"(d[69]), "+f"(d[70]), "+f"(d[71]),
      "+f"(d[72]), "+f"(d[73]), "+f"(d[74]), "+f"(d[75]), "+f"(d[76]), "+f"(d[77]), "+f"(d[78]), "+f"(d[79]),
      "+f"(d[80]), "+f"(d[81]), "+f"(d[82]), "+f"(d[83]), "+f"(d[84]), "+f"(d[85]), "+f"(d[86]), "+f"(d[87]),
      "+f"(d[88]), "+f"(d[89]), "+f"(d[90]), "+f"(d[91]), "+f"(d[92]), "+f"(d[93]), "+f"(d[94]), "+f"(d[95])
    : "r"(a[0]), "r"(a[1]), "r"(a[2]), "r"(a[3]), "l"(db), "r"(add));
}
__device__ __forceinline__ void wgmma_n48(float (&d)[24], const uint32_t (&a)[4], uint64_t db, int add) {
  asm volatile("{.reg .pred p; setp.ne.b32 p, %29, 0; wgmma.mma_async.sync.aligned.m64n48k16.f32.bf16.bf16 "
    "{%0, %1, %2, %3, %4, %5, %6, %7, %8, %9, %10, %11, %12, %13, %14, %15, "
    "%16, %17, %18, %19, %20, %21, %22, %23}, "
    "{%24, %25, %26, %27}, %28, p, 1, 1, 1;}"
    : "+f"(d[0]), "+f"(d[1]), "+f"(d[2]), "+f"(d[3]), "+f"(d[4]), "+f"(d[5]), "+f"(d[6]), "+f"(d[7]),
      "+f"(d[8]), "+f"(d[9]), "+f"(d[10]), "+f"(d[11]), "+f"(d[12]), "+f"(d[13]), "+f"(d[14]), "+f"(d[15]),
      "+f"(d[16]), "+f"(d[17]), "+f"(d[18]), "+f"(d[19]), "+f"(d[20]), "+f"(d[21]), "+f"(d[22]), "+f"(d[23])
    : "r"(a[0]), "r"(a[1]), "r"(a[2]), "r"(a[3]), "l"(db), "r"(add));
}
__device__ __forceinline__ void wgmma_n80(float (&d)[40], const uint32_t (&a)[4], uint64_t db, int add) {
  asm volatile("{.reg .pred p; setp.ne.b32 p, %45, 0; wgmma.mma_async.sync.aligned.m64n80k16.f32.bf16.bf16 "
    "{%0, %1, %2, %3, %4, %5, %6, %7, %8, %9, %10, %11, %12, %13, %14, %15, "
    "%16, %17, %18, %19, %20, %21, %22, %23, %24, %25, %26, %27, %28, %29, %30, %31, "
    "%32, %33, %34, %35, %36, %37, %38, %39}, "
    "{%40, %41, %42, %43}, %44, p, 1, 1, 1;}"
    : "+f"(d[0]), "+f"(d[1]), "+f"(d[2]), "+f"(d[3]), "+f"(d[4]), "+f"(d[5]), "+f"(d[6]), "+f"(d[7]),
      "+f"(d[8]), "+f"(d[9]), "+f"(d[10]), "+f"(d[11]), "+f"(d[12]), "+f"(d[13]), "+f"(d[14]), "+f"(d[15]),
      "+f"(d[16]), "+f"(d[17]), "+f"(d[18]), "+f"(d[19]), "+f"(d[20]), "+f"(d[21]), "+f"(d[22]), "+f"(d[23]),
      "+f"(d[24]), "+f"(d[25]), "+f"(d[26]), "+f"(d[27]), "+f"(d[28]), "+f"(d[29]), "+f"(d[30]), "+f"(d[31]),
      "+f"(d[32]), "+f"(d[33]), "+f"(d[34]), "+f"(d[35]), "+f"(d[36]), "+f"(d[37]), "+f"(d[38]), "+f"(d[39])
    : "r"(a[0]), "r"(a[1]), "r"(a[2]), "r"(a[3]), "l"(db), "r"(add));
}

__device__ __forceinline__ constexpr int wo_off(int i) { return (i < 4 ? 8 + i : i - 4) * WO; }
__device__ __forceinline__ void load_stage(const Params& P, uint32_t sb, int st, int j, int g, int rank) {
  const uint32_t fb = sb + OFF_BAR + 8 * (B_FULL + (st & 3)), a = sb + (st & 3) * STAGE;
  mbar_expect_tx(fb, STAGE);
  tma2(a, &P.xa, fb, 640 * rank + 64 * st, 128 * j);
  tma3_both(a + STAGE_A + rank * (STAGE_B0 / 2), &P.w0, fb, 80 * g, 64 * st + 32 * rank, 0);
  tma3_both(a + STAGE_A + STAGE_B0 + rank * (STAGE_B1 / 2), &P.w1, fb, 80 * g + 64, 64 * st + 32 * rank, 0);
}

__device__ __forceinline__ void run_producer(const Params& P, uint8_t* sm, uint32_t sb, int b, uint32_t t0) {
  const int rank = b & 1, g = (b >> 1) & 7, j = b >> 4;
  const uint32_t bar = sb + OFF_BAR;
#pragma unroll 1
  for (int st = 1; st < 10; ++st) {
    if (st == 2) {
      wait_until(t0 + WPF_AT);
      if (elect_one()) bulk_prefetch(P.wqkv + (128 + 4 * b) * 1920, 15360);
      bar_sync<NB_GO, 160>();
    }
    if (st == 9) bar_sync<NB_HELP, 128>();
    mbar_wait(bar + 8 * (B_EMPTY + (st & 3)), (((st + 1) >> 2) + 1) & 1);
    if (elect_one()) {
      load_stage(P, sb, st, j, g, rank);
      const int k = st - LMPF_AT;
      if ((uint32_t)k < 5u) bulk_prefetch(P.wmod + (5 * b + k) * 3840 + 1280, 5120);
      if (st == 7) bulk_prefetch(P.wo + b * 3200, 6400);
    }
  }
  TSTAMP(1);
#pragma unroll 1
  for (int i = 0; i < 8; ++i) {
    if (i < 2 || i == 4 || i == 7) mbar_wait(bar + 8 * (B_EMPTY + (i < 2 ? 2 + i : i & 1)), i == 0);
    if (elect_one()) {
      const uint32_t fb = bar + 8 * (i ? B_WO1 : B_WO0), a = sb + (i < 4 ? 8 + i : i - 4) * WO;
      if (i == 0) {
        mbar_expect_tx(bar + 8 * B_XS, 25600);
        tma2(sb + OFF_LM, &P.wm, bar + 8 * B_XS, 1280 + 80 * (b & 31), 160 * (b >> 5));
      }
      if (i < 2) mbar_expect_tx(fb, i ? 7 * 12800 : 12800);
      if ((i & 1) == rank) {
        const int k0 = 80 * (i ? i - (i <= g) : g);
        tma3_both(a, &P.woa, fb, 80 * g, k0, 0);
        tma2_both(a + 10240, &P.wob, fb, 80 * g + 64, k0);
      }
    }
  }
  TSTAMP(3);
  if (b < N_FFN) {
    if (elect_one()) {
      mbar_expect_tx(bar + 8 * B_ACT, 1024);
      mbar_expect_tx(bar + 8 * B_FFN, 40960);
    }
    uint32_t next = clock32();
#pragma unroll 1
    for (int i = 0; i < 6; ++i) {
      if (i == FFN_EARLY) {
        mbar_wait(bar + 8 * B_GO, 1);
        next = clock32();
      }
      if (i == 3) bar_sync<NB_LM, 128>();
      if (i == 4) next += DOWN_GAP;
      wait_until(next);
      next += FFN_GAP;
      if (elect_one())
        tma3(sb + OFF_FFN + 10240 * i, &P.wg + (i >> 1), bar + 8 * (i < 4 ? B_FFN : B_XS), i < 4 ? 32 * (b >> 1) : 0, i < 4 ? 0 : 16 * b, i < 4 ? 2 * rank + (i & 1) : 5 * (i & 1));
    }
  }
  TSTAMP(4);
}

__device__ __forceinline__ void run_helper(const Params& P, uint8_t* sm, uint32_t sb, int b, int hw, uint32_t ep, int budget, uint32_t poll_at) {
  const int h = threadIdx.x - 256, lane = h & 31, gq = lane >> 2, t = lane & 3, rank = b & 1, g = (b >> 1) & 7, j = b >> 4;
  const uint32_t bar = sb + OFF_BAR, prm = sb + OFF_PRM;
  uint4* const box = P.sc + b * BOX;
  const bool main20 = lane < 20;
  const int fin = 128 * (b >> 4) + 16 * ((b >> 2) & 3) + 2 * (b & 3) + (lane & 1) + 32 * (lane & 2) + 2 * (lane & 4);
  const int which = main20 ? 2 - hw : 3, fsl = (fin * 205) >> 14;
  const int q4 = main20 ? lane : hw < 2 ? min(10 * hw + lane - 20, 19) : (fin - 80 * fsl) >> 2;
  uint32_t wr[2];
  asm volatile("ld.global.nc.v2.u32 {%0, %1}, [%2];" : "=r"(wr[0]), "=r"(wr[1]) : "l"(P.wr + 80 * g + 4 * q4));
  uint32_t cw;
  asm volatile("ld.global.nc.u32 %0, [%1];" : "=r"(cw) : "l"(P.c + 160 * (b >> 5) + 2 * min(h, 79)));
  sts1(sb + OFF_SILU + 4 * min(h, 79), pack2(bf_lo(cw) * sigmoid(bf_lo(cw)), bf_hi(cw) * sigmoid(bf_hi(cw))));
  if (h < 4) sts1(prm + R_ONE + 4 * h, 0x3F803F80u);
  wait_until(poll_at);
  {
    uint32_t v[4][4];
    const int h80 = min(h, 79);
    const uint4* src = at<16>(P.sc, (h80 >> 2) * BOX + 4 * j + (h80 & 3));
#pragma unroll 1
    do {
#pragma unroll
      for (int i = 0; i < 4; ++i) ld_rlx4(v[i], src + i * 20 * BOX);
    } while (retry<~0u>(stale<4, 2>(v, ep), budget));
#pragma unroll
    for (int i = 0; i < 4; ++i) sts2(sb + OFF_C1 + 16 * h80 + 1280 * (i & 1) + (i < 2 ? 8 : 0), v[i][0], v[i][1]);
    mbar_arrive(bar + 8 * B_TAB);
  }
  TSTAMP(3);
  bar_sync<NB_GO, 160>();
  {
    const char* src = hw == 2 ? at<128>(reinterpret_cast<const char*>(P.wdown), 160 * b + lane)
                              : at<128>(reinterpret_cast<const char*>(hw ? P.wup : P.wgate), (160 * (b & 3) + lane) * 27 + (b >> 2));
    uint4* slot = at<16>(box + M_HALO, h);
    uint32_t next = clock32() + TOUCH_AT + hw * (TOUCH_GAP / 3);
#pragma unroll 1
    for (int i = 0; i < 5; ++i) {
      wait_until(next);
      next += TOUCH_GAP;
      if (b < N_FFN) asm volatile("cp.async.cg.shared.global.L2::128B [%0], [%1], 16;" ::"r"(sb + OFF_SINK + 16 * h), "l"(src) : "memory");
      src += hw == 2 ? 4096 : 32 * 3456;
      if (i < 4) {
        st_rlx4(slot, ~ep, ~ep, ~ep, ~ep);
        st_rlx4(slot + 96, ~ep, ~ep, ~ep, ~ep);
      }
      slot += 192;
    }
  }
  bar_sync<NB_HELP, 128>();
  TSTAMP(5);

  {
    float d0[4] = {0.f, 0.f, 0.f, 0.f}, d1[4] = {0.f, 0.f, 0.f, 0.f};
    uint32_t wa = sb + OFF_LM + (8 * (lane >> 4) + (lane & 7)) * 160 + 64 * hw + (lane & 8) * 2, sa = sb + OFF_SILU + (lane >> 3) * 16;
    mbar_wait(bar + 8 * B_XS, 1);
    {
      uint32_t hv[2][4] = {};
      const int q = min(2 * hw, 3);
      const uint4* const src = at<16>(box + (M_HALO - 16 * BOX), 32 * q + lane);
      mbar_wait(bar + 8 * B_EMPTY, 0);
      wait_until(clock32() + HALO_GAP);
      if (j > 0) gather<2, 32, 0>(hv, src, ep, budget);
      stsm4(sb + OFF_H + 512 * q + 16 * lane, hv[0]);
      stsm4(sb + OFF_H + 512 * q + 16 * lane + 512, hv[1]);
      bar_arrive<NB_HALO, 128>();
      if (j > 0) TSTAMP(4);
    }
    mbar_wait(bar + 8 * (B_EMPTY + 1), 0);
    TSTAMP(6);
#pragma unroll 1
    for (int u = 0; u < 5; ++u) {
      uint32_t a[4][4], s[4];
      ldsm4(s, sa);
#pragma unroll
      for (int i = 0; i < 4; ++i) ldsm4t(a[i], wa + (i >> 1) * 2560 + (i & 1) * 32);
      mma16(d0, a[0], s[0], s[1], d0);
      mma16(d1, a[1], s[0], s[1], d1);
      mma16(d0, a[2], s[2], s[3], d0);
      mma16(d1, a[3], s[2], s[3], d1);
      wa += 5120;
      sa += 64;
    }
    const float v = t & 2 ? (t & 1 ? d1[2] : d1[0]) : (t & 1 ? d0[2] : d0[0]);
    if (32 * hw + 8 * t < 80) st_rlx1(at<4>(box + M_LATE, 32 * hw + 8 * t + gq), tag(u32(v), ep));
  }
  if (b < N_FFN) {
    if (h == 0) mbar_expect_tx(bar + 8 * B_XS, 20480);
    bar_arrive<NB_LM, 128>();
  }
  TSTAMP(7);
  wait_until(clock32() + LATE_GAP);
  {
    uint32_t v[4][4];
    const uint4* src = at<16>(P.sc + M_LATE, (8 * which + (main20 || hw < 2 ? g : fsl & 7)) * BOX + q4);
#pragma unroll 1
    do {
#pragma unroll
      for (int i = 0; i < 4; ++i) ld_rlx4(v[i], src + i * 32 * BOX);
    } while (retry<1>(stale<4, 0>(v, ep) | stale<4, 1>(v, ep) | stale<4, 2>(v, ep) | stale<4, 3>(v, ep), budget));
    const uint32_t one = which == 2 ? 0x3F803F80u : 0u;
    uint32_t w[2], pw[2];
#pragma unroll
    for (int e = 0; e < 2; ++e) {
      w[e] = fma2(pack2(f32(v[0][2 * e]) + f32(v[1][2 * e]) + f32(v[2][2 * e]) + f32(v[3][2 * e]),
                        f32(v[0][2 * e + 1]) + f32(v[1][2 * e + 1]) + f32(v[2][2 * e + 1]) + f32(v[3][2 * e + 1])), 0x3F803F80u, one);
      pw[e] = fma2(w[e], wr[e], 0x80008000u);
    }
    const uint32_t dst = prm + (main20 || hw < 2 ? 160 * which + 8 * q4 : R_FIN + 4 * (lane & 6));
    sts2(dst, w[0], w[1]);
    sts2(dst + 800, pw[0], pw[1]);
    float s = main20 ? bf_lo(pw[0]) + bf_hi(pw[0]) + bf_lo(pw[1]) + bf_hi(pw[1]) : 0.f;
#pragma unroll
    for (int o = 16; o > 0; o >>= 1) s += shx(s, o);
    sts1(sb + OFF_KEY + 64 + 4 * hw, u32(s));
    mbar_arrive(bar + 8 * B_TAB);
    mbar_wait(bar + 8 * B_TAB, 1);
  }
  TSTAMP(8);

  uint32_t ckey = 0;
  uint4* const odst = reinterpret_cast<uint4*>(P.out + (256 * j + rank) * 640 + 80 * g);
  if (hw == 0) {
    const uint32_t tile = min(4 * (lane & 3) + (lane >> 3), 9) * 16;
    uint32_t c1[4], sv[4], gb[4], x[4];
    ldsm4(c1, prm + R_C1 + tile);
    ldsm4(sv, prm + R_SB + tile);
    ldsm4(gb, prm + (lane & 4 ? R_GB + tile : R_ONE));
    const uint32_t bc = lds1(sb + OFF_KEY + 68), keep = gq & 4 ? ~0u : 0u;
    uint4* const cdst = at<16>(P.sc + M_CAND, (b - rank + (lane >> 4)) * BOX + 2 * (lane & 12) + 4 * rank + (lane & 3));
    uint32_t crow;
    {
      bar_sync<NB_KEY, 288>();
      uint32_t k0, k1;
      asm volatile("ld.shared.v2.u32 {%0, %1}, [%2];" : "=r"(k0), "=r"(k1) : "r"(sb + OFF_KEY + 8 * (lane & 7)) : "memory");
      ckey = __reduce_max_sync(0xFFFFFFFFu, k0);
      crow = (~ckey >> 1) & 127;
      TSTAMP(9);
      ldsm4(x, sb + OFF_X2 + crow * 176 + tile);
      const uint32_t nw = __shfl_sync(0xFFFFFFFFu, k1, crow >> 4), rs = dup_hi(nw), nm = dup_lo(nw);
#pragma unroll
      for (int e = 0; e < 4; ++e) x[e] = fma2(gb[e], fma2(fma2(x[e], rs, nm), c1[e], sv[e]), x[e] & keep);
      st_rlx4(cdst, tag(x[0], ep), x[1], gq == 2 ? ckey : x[2], gq == 2 ? bc : x[3]);
    }
    bar_arrive<NB_PUB, 288>();
    TSTAMP(10);
    bar_sync<NB_OUT + 1, 160>();
    uint32_t next = clock32() + OUT_AT;
#pragma unroll 1
    for (int u = 0; u < 8; ++u) {
      if (u == 4) {
        bar_sync<NB_OUT, 160>();
        next = clock32();
      }
      wait_until(next);
      next += OUT_GAP;
      if (u != crow >> 4 && elect_one())
        asm volatile("cp.async.bulk.tensor.2d.global.shared::cta.bulk_group [%0, {%2, %3}], [%1];"
                     ::"l"(&P.om), "r"(sb + OFF_OUT + 2560 * u), "r"(640 * rank + 80 * g), "r"(128 * j + 16 * u) : "memory");
    }
    asm volatile("cp.async.bulk.commit_group;" ::: "memory");
    TSTAMP(11);
  } else {
    if (b >= 80 || hw == 2) return;
    bar_sync<NB_WIN, 64>();
  }
  uint32_t m[7][4], wkey = lds1(sb + OFF_KEY + 80);
  if (b >= N_FFN) {
    gather<1, 0, 0>(m, at<64>(P.sc + M_CAND + 16, (lane & 14) * (2 * BOX) + (lane & 1)), ep, budget);
    wkey = __reduce_max_sync(0xFFFFFFFFu, m[0][2]);
  }
  const uint32_t wtok = ~wkey & 2047;
  TSTAMP(12);
  if (hw == 0) {
    const uint32_t u = (~ckey >> 5) & 7, skip = ckey == wkey ? (~ckey >> 1) & 15 : 16;
#pragma unroll
    for (int i = 0; i < 5; ++i) {
      const uint32_t v = lane + 32 * i, r = (v * 205) >> 11;
      if (r != skip) *at<16>(odst, 2560 * u + v + 150 * r) = *reinterpret_cast<const uint4*>(sm + OFF_OUT + 2560 * u + 16 * v);
    }
    st_rlx1(at<4>(box + M_EPOCH, lane), ep);
    asm volatile("cp.async.bulk.wait_group.read 0;" ::: "memory");
    TSTAMP(15);
    TALIGN(1);
    return;
  } else {
    const int cn = fin - 80 * fsl;
    gather<1, 0, 0>(m, at<16>(P.sc + M_CAND, (16 * (wtok >> 8) + (lane & 8 ? 2 * (lane & 7) : 2 * fsl + 1)) * BOX + 4 * (wtok & 1) +
                                             (lane & 8 ? 16 : 8 * (cn >> 5) + ((cn >> 1) & 3))), ep, budget);
    const uint32_t bw = cn & 16 ? (cn & 8 ? m[0][3] : m[0][2]) : (cn & 8 ? m[0][1] : m[0][0]);
    const uint32_t gw = lds1(prm + R_FIN + 4 * (lane & 6) + 4 * (b & 1));
    float r = f32(m[0][3]);
#pragma unroll
    for (int o = 1; o < 8; o <<= 1) r += shx(r, o);
    r = __shfl_sync(0xFFFFFFFFu, r, 8) + f32(wkey >> 31 ? wkey & 0x7FFFF800u : ~wkey | 0x7FFu);
    const float sg = bf_round(sigmoid(bf_round(r))), gv = lane & 1 ? bf_hi(gw) : bf_lo(gw), bv = lane & 1 ? bf_hi(bw) : bf_lo(bw);
    __nv_bfloat16* const dst = at<2>(P.out, wtok * 640 + fin);
    const uint4* const src = at<16>(P.sc + M_YP, (4 * (lane >> 3) + ((b >> 2) & 3)) * BOX + 32 * j + 8 * (b & 3) + (lane & 7));
    TSTAMP(13);
    bar_sync<NB_YP, 64>();
    wait_until(clock32() + YP_GAP);
    gather_lazy<7, 16 * BOX, 32 * BOX, 0>(m, src, ep, budget, lane >= 24);
    TSTAMP(14);
    float y[4];
#pragma unroll
    for (int e = 0; e < 4; ++e)
      y[e] = ((f32(m[0][e]) + f32(m[1][e])) + (f32(m[2][e]) + f32(m[3][e]))) + ((f32(m[4][e]) + f32(m[5][e])) + f32(m[6][e]));
    const bool u1 = lane & 2, u2 = lane & 4;
    const float e0 = (u1 ? y[1] : y[0]) + shx(u1 ? y[0] : y[1], 2), e1 = (u1 ? y[3] : y[2]) + shx(u1 ? y[2] : y[3], 2);
    float e = (u2 ? e1 : e0) + shx(u2 ? e0 : e1, 4);
    e += shx(e, 8);
    e += shx(e, 16);
    asm volatile("{.reg .pred p; setp.lt.u32 p, %2, 8; @p st.global.b16 [%0], %1;}"
                 ::"l"(dst), "h"((uint16_t)pack2(fmaf(gv, bf_round(bf_round(e) * sg), bv), 0.f)), "r"(lane) : "memory");
  }
  TSTAMP(15);
}

#define ACC(part, i, e) ((i) < 8 ? accA[32 * (part) + 4 * ((i) & 7) + (e)] : accB[8 * (part) + 4 * ((i) & 1) + (e)])
__device__ __forceinline__ constexpr int kpos(int i) { return i == 2 ? 8 : i == 7 ? 9 : i - (i > 2) - (i > 7); }

__device__ __forceinline__ void run_consumer(const Params& P, uint8_t* sm, uint32_t sb, int b, int warp, uint32_t ep, int budget) {
  const int tid = threadIdx.x, lane = tid & 31, gq = lane >> 2, t = lane & 3, p = warp >> 2, wq = warp & 3, rb = warp ^ 4;
  const int rank = b & 1, g = (b >> 1) & 7, j = b >> 4;
  const uint32_t bar = sb + OFF_BAR;
  uint4* const box = P.sc + b * BOX;
  const float z4[4] = {0.f, 0.f, 0.f, 0.f};

  uint32_t nrm[4];
  {
    uint32_t x[5][4], ones[10];
#pragma unroll
    for (int i = 0; i < 10; ++i) ones[i] = 0x3F803F80u;
    uint4* const dst = at<8>(box + M_ST1, tid >> 4);
    mbar_wait(bar + 8 * B_XS, 0);
    asm volatile("cp.async.wait_all;" ::: "memory");
    TSTAMP(4);
#pragma unroll
    for (int i = 0; i < 5; ++i) lds4(x[i], sb + OFF_XS + 4096 * i + 16 * tid);
    float s[4], qlo, qhi, mean, rstd;
    row_stats(s, qlo, qhi, x, ones, gq);
    const float q = __shfl_sync(0xFFFFFFFFu, qlo + qhi, 4 * gq + (gq >> 1));
    float v = t & 1 ? q : s[0] + s[2];
    v += shx(v, 4);
    v += shx(v, 8);
    const uint32_t nw = norm_word(v, shx(v, 1), mean, rstd);
    if ((lane & 15) == 0) st_rlx2(dst, nw, ep);
    TSTAMP(5);
    asm volatile("setmaxnreg.inc.sync.aligned.u32 224;");
  }

  float accA[96], accB[24];
#pragma unroll
  for (int i = 0; i < 96; ++i) asm volatile("" : "=f"(accA[i]));
#pragma unroll
  for (int i = 0; i < 24; ++i) asm volatile("" : "=f"(accB[i]));
  uint32_t xr[5][4];
#pragma unroll
  for (int i = 0; i < 20; ++i) asm volatile("" : "=r"(xr[i >> 2][i & 3]));
  const uint32_t turn = keep(NB_TURN + (tid >> 7)), pass = keep(NB_TURN + 1 - (tid >> 7));
  uint4* const opub = reinterpret_cast<uint4*>(__shfl_xor_sync(0xFFFFFFFFu, reinterpret_cast<uintptr_t>(at<16>(box + M_O, tid ^ 2)), 2));
  const uint4* src[7];
  const uint4* const lower = reinterpret_cast<const uint4*>(__shfl_xor_sync(0xFFFFFFFFu, reinterpret_cast<uintptr_t>(at<16>(P.sc + M_O, (b & ~14) * BOX + (tid ^ 2))), 2));
  const int l2 = lane ^ 2;
  const uint32_t ha = keep(sb + OFF_H + rb * 2560 + 16 * l2), lo = keep(sb + OFF_L + rb * 1280 + 16 * l2);
  const uint32_t va = keep(sb + OFF_H + 1280 + (rb + ((lane >> 3) & 1)) * 2560 + (lane >> 4) * 128 + (l2 & 7) * 16);
  const uint32_t M = keep((2 * (t ^ 2) > gq ? 0xFFFFu : 0u) | (2 * (t ^ 2) + 1 > gq ? 0xFFFF0000u : 0u)), gk = keep(g + (tid >> 9));
  {
    uint32_t la = sb + (16 * rb + (lane & 15)) * 128 + (((lane >> 4) ^ (lane & 7)) << 4), c1a = sb + OFF_C1 + 16 * t;
    const uint32_t rel = keep(map_to_cta(bar + 8 * B_EMPTY + 16, lane & 1)), y0 = keep(8 * ((5 * g >> 2) + 1) + (tid >> 9));
    const bool two = (ha & 0x1E0) == 0;
    const uint64_t dbase = make_desc(sb + STAGE_A, 4096, 1024, 1);
    uint64_t d0 = dbase;
    uint32_t raw[4][4], cw[4][4], y = 8;
    int add = 0;
    if (p == 1) turn_pass(pass);
    {
      const uint4* const src = at<8>(P.sc + M_ST1, (16 * j + 2 * rb) * 2 * BOX + 2 * gq + rank);
      mbar_wait(bar + 8 * B_FULL, 0);
#pragma unroll
      for (int k = 0; k < 4; ++k) ldsm4(raw[k], la ^ (32 * k));
      uint32_t n0[2], n1[2];
#pragma unroll 1
      do {
        ld_rlx2(n0, src);
        ld_rlx2(n1, src + BOX);
      } while (retry<~0u>(neq2(n0[1], n1[1], ep), budget));
      TSTAMP(6);
      mbar_wait(bar + 8 * B_TAB, 0);
#pragma unroll
      for (int k = 0; k < 4; ++k) lds4(cw[k], c1a + 64 * k);
      if (warp == 0) bar_arrive<NB_GO, 160>();
      nrm[0] = dup_hi(n0[0]); nrm[1] = dup_hi(n1[0]); nrm[2] = dup_lo(n0[0]); nrm[3] = dup_lo(n1[0]);
    }
    TSTAMP(7);
#pragma unroll 1
    for (;;) {
      uint32_t af[4][4];
      c1a += 256;
#pragma unroll
      for (int k = 0; k < 16; ++k) raw[k >> 2][k & 3] = fma2(raw[k >> 2][k & 3], nrm[k & 1], nrm[2 + (k & 1)]);
      wg_wait();
      if (two) mbar_arrive_cluster(rel ^ (y & 24));
#pragma unroll
      for (int k = 0; k < 16; ++k) af[k >> 2][k & 3] = fma2(raw[k >> 2][k & 3], cw[k >> 2][(k >> 1) & 1], cw[k >> 2][2 + ((k >> 1) & 1)]);
#pragma unroll
      for (int k = 0; k < 4; ++k) lds4(cw[k], c1a + 64 * k);
      wg_fence();
      turn_wait(turn);
      constexpr uint64_t D1 = (STAGE_B0 >> 4) + ((uint64_t)64 << 16) - ((uint64_t)256 << 16) + ((uint64_t)16 << 32) - ((uint64_t)64 << 32) + ((uint64_t)2 << 62);
#pragma unroll
      for (int k = 0; k < 4; ++k) {
        wgmma_n192(accA, af[k], d0 + ((k >> 1) * (STAGE_B0 / 2) + (k & 1) * 2048 >> 4), k ? 1 : add);
        if (PASS1 == 2 * k) turn_pass(pass);
        wgmma_n48(accB, af[k], d0 + (D1 + ((k >> 1) * (STAGE_B1 / 2) + (k & 1) * 512 >> 4)), k ? 1 : add);
        if (PASS1 == 2 * k + 1) turn_pass(pass);
      }
      wg_commit();
      if (__any_sync(0xFFFFFFFFu, y - y0 < 16u)) {
#pragma unroll
        for (int i = 0; i < 5; ++i) {
          const uint32_t k = 160 * g + 32 * i + 128 - 16 * y;
          if (k < 128u) ldsm4(xr[i], la ^ k);
        }
      }
      if (y == 80) break;
      const bool wrap = (uint32_t)d0 == (uint32_t)dbase + (3 * STAGE >> 4);
      la += wrap ? -3 * STAGE : STAGE;
      d0 = wrap ? dbase : d0 + (STAGE >> 4);
      add = 1;
      mbar_wait(bar + (y & 24), (y >> 5) & 1);
#pragma unroll
      for (int k = 0; k < 4; ++k) ldsm4(raw[k], la ^ (32 * k));
      y += 8;
    }
    wg_wait();
    if (two) mbar_arrive_cluster(rel - 8);
  }
  TSTAMP(8);

  uint32_t o[5][4];
  {
    uint32_t hi[20], vl[10], kl[10], kh[10], vv[20], qf[4][4], qs[4][2];
#pragma unroll
    for (int i = 0; i < 10; ++i) {
      hi[kpos(i)] = pack2(ACC(1, i, 2), ACC(1, i, 3));
      hi[10 + i] = pack2(ACC(2, i, 2), ACC(2, i, 3));
    }
#pragma unroll
    for (int q = 0; q < 5; ++q) hi[4 * q] = tag(hi[4 * q], ep);
    if (rb == 7) {
#pragma unroll
      for (int q = 0; q < 5; ++q) st_rlx4(opub + (M_HALO - M_O - 96 + 32 * q), hi + 4 * q);
    }
    if (HALO_FENCE) sched_fence(P.zero);
    TSTAMP(29);
#pragma unroll
    for (int i = 0; i < 10; ++i) kl[kpos(i)] = pack2(ACC(1, i, 0), ACC(1, i, 1));
#pragma unroll
    for (int hd = 0; hd < 4; ++hd) {
      const int f0 = 5 * (hd >> 1) + 3 * (hd & 1), sg = 5 * (hd >> 1) + 2;
      const bool mine = (t >> 1) == (hd & 1);
#pragma unroll
      for (int e = 0; e < 4; ++e) qf[hd][e] = pack2(ACC(0, f0 + (e >> 1), 2 * (e & 1)), ACC(0, f0 + (e >> 1), 2 * (e & 1) + 1));
#pragma unroll
      for (int e = 0; e < 2; ++e) {
        if (!(hd & 1)) qs[hd + 1][e] = pack2(ACC(0, sg, 2 * e), ACC(0, sg, 2 * e + 1));
        qs[hd][e] = mine ? qs[hd | 1][e] : 0u;
      }
    }
    sched_fence(P.zero);
#pragma unroll
    for (int q = 0; q < 5; ++q) stsm4(ha + 2560 + 512 * q, hi + 4 * q);
#pragma unroll
    for (int i = 0; i < 10; ++i) vl[i] = pack2(ACC(2, i, 0), ACC(2, i, 1));
    stsm4(lo, vl);
    stsm4(lo + 512, vl + 4);
    stsm2(lo + 1024, vl + 8);
    __syncwarp();
    if (lane == 0) mbar_arrive(bar + 8 * B_HALO);
    float S0[4][4], S1[4][4], S2[4][4];
    ldsm4t(vl, lo);
    ldsm4t(vl + 4, lo + 512);
    ldsm2t(vl + 8, lo + 1024);
#pragma unroll
    for (int hd = 0; hd < 4; ++hd) {
      mma16(S1[hd], qf[hd], kl[2 * hd], kl[2 * hd + 1], z4);
      mma16(S2[hd], qf[hd], hi[2 * hd], hi[2 * hd + 1], z4);
    }
#pragma unroll
    for (int hd = 0; hd < 4; ++hd) {
      mma8(S1[hd], qs[hd][0], qs[hd][1], kl[8 + (hd >> 1)], S1[hd]);
      mma8(S2[hd], qs[hd][0], qs[hd][1], hi[8 + (hd >> 1)], S2[hd]);
    }
    const bool up0 = M == ~0u, up1 = M != 0;
    uint32_t pp[4][2];
    const auto softmax = [&](const float (&A)[4][4], const float (&B)[4][4], int e) {
      const float SC = 0.22360679774997896f * 1.4426950408889634f;
      float a[4][2], mx[4];
#pragma unroll
      for (int hd = 0; hd < 4; ++hd) {
        a[hd][0] = up0 ? A[hd][2 * e] : B[hd][2 * e];
        a[hd][1] = up1 ? A[hd][2 * e + 1] : B[hd][2 * e + 1];
        mx[hd] = fmaxf(a[hd][0], a[hd][1]);
      }
#pragma unroll
      for (int s = 1; s < 4; s <<= 1) {
#pragma unroll
        for (int hd = 0; hd < 4; ++hd) mx[hd] = fmaxf(mx[hd], shx(mx[hd], s));
      }
#pragma unroll
      for (int hd = 0; hd < 4; ++hd) {
        const float ms = mx[hd] * -SC;
        pp[hd][e] = pack2(ex2(fmaf(a[hd][0], SC, ms)), ex2(fmaf(a[hd][1], SC, ms)));
      }
    };
    if (HI_FIRST) softmax(S1, S2, 1);
#pragma unroll
    for (int i = 0; i < 7; ++i)
      asm volatile("{.reg .pred p; setp.gt.u32 p, %1, %2; selp.b64 %0, %3, %4, p;}" : "=l"(src[i]) : "r"(gk), "r"(i), "l"(lower), "l"(lower + 2 * BOX));
    if (HI_FIRST) sched_fence(P.zero);
    TSTAMP(9);
    mbar_wait(bar + 8 * B_HALO, 0);
    if (rb == 0) bar_sync<NB_HALO, 128>();
    TSTAMP(10);
    ldsm4(kh, ha);
    ldsm4(kh + 4, ha + 512);
    ldsm2(kh + 8, ha + 1024);
#pragma unroll
    for (int i = 0; i < 5; ++i) ldsm4t(vv + 4 * i, va + 256 * i);
    const float ev = (j | rb) == 0 ? -1e9f / 0.22360679774997896f : 0.f, e4[4] = {ev, ev, ev, ev};
#pragma unroll
    for (int hd = 0; hd < 4; ++hd) mma16(S0[hd], qf[hd], kh[2 * hd], kh[2 * hd + 1], e4);
#pragma unroll
    for (int hd = 0; hd < 4; ++hd) mma8(S0[hd], qs[hd][0], qs[hd][1], kh[8 + (hd >> 1)], S0[hd]);
    if (!HI_FIRST) softmax(S1, S2, 1);
    softmax(S0, S1, 0);
    float L[4][4], O[4][3][4];
#pragma unroll
    for (int hd = 0; hd < 4; ++hd) mma8(L[hd], pp[hd][0], pp[hd][1], 0x3F803F80u, z4);
#pragma unroll
    for (int hd = 0; hd < 4; ++hd) {
      const uint32_t p0 = pp[hd][0] & M, p2 = pp[hd][0] & ~M, p3 = pp[hd][1] & M, p5 = pp[hd][1] & ~M;
      const uint32_t z0 = pp[hd][0] & P.zero, z1 = pp[hd][1] & P.zero;
#pragma unroll
      for (int e = 0; e < 3; ++e) {
        const int f = 5 * (hd >> 1) + 2 * (hd & 1) + e;
        mma16(O[hd][e], p0, z0, z1, p5, vv[2 * f], vv[2 * f + 1], z4);
      }
#pragma unroll
      for (int e = 0; e < 3; ++e) mma8(O[hd][e], p2, p3, vl[5 * (hd >> 1) + 2 * (hd & 1) + e], O[hd][e]);
    }
    const bool odd = t >> 1;
#pragma unroll
    for (int hp = 0; hp < 2; ++hp) {
      const float (&A)[3][4] = O[2 * hp];
      const float (&B)[3][4] = O[2 * hp + 1];
#pragma unroll
      for (int e = 0; e < 2; ++e) {
        const float ra = rcp(L[2 * hp][2 * e]), rc = rcp(L[2 * hp + 1][2 * e]), rm = odd ? rc : ra;
        uint32_t* const d = &o[0][0] + 10 * hp + e;
        d[0] = pack2(A[0][2 * e] * ra, A[0][2 * e + 1] * ra);
        d[2] = pack2(A[1][2 * e] * ra, A[1][2 * e + 1] * ra);
        d[4] = pack2((odd ? B[0][2 * e] : A[2][2 * e]) * rm, (odd ? B[0][2 * e + 1] : A[2][2 * e + 1]) * rm);
        d[6] = pack2(B[1][2 * e] * rc, B[1][2 * e + 1] * rc);
        d[8] = pack2(B[2][2 * e] * rc, B[2][2 * e + 1] * rc);
      }
      if (hp == 0) {
#pragma unroll
        for (int s = 0; s < 2; ++s) {
          o[s][0] = tag(o[s][0], ep);
          st_rlx4(opub + 256 * s, o[s]);
        }
        sched_fence(P.zero);
        if (p == 1) bar_arrive<NB_PV, 256>();
      }
    }
#pragma unroll
    for (int s = 2; s < 5; ++s) o[s][0] = tag(o[s][0], ep);
  }
  TSTAMP(11);

  float acc[40];
#pragma unroll
  for (int i = 0; i < 40; ++i) asm volatile("" : "=f"(acc[i]));
  uint32_t ga[10], pb[10], uw;
  uint4* const sdst = at<16>(box + M_ST2, 16 * rb + gq);
  const uint32_t prow = sb + OFF_PRM + (lane >> 3) * 16;
  {
    const uint64_t dw = make_desc(sb, 5120, 512, 2);
    uint32_t in[5][7][4];
    const auto fetch = [&](int s) {
#pragma unroll
      for (int i = 0; i < 7; ++i) ld_rlx4(in[s][i], src[i] + (2 * BOX * i + 256 * s));
    };
    st_rlx4(opub + 256 * 2, o[2]);
    mbar_wait(bar + 8 * B_WO0, 0);
    if (p == 0) bar_sync<NB_PV, 256>();
    fetch(0);
    if (PUB34 == 0) {
      st_rlx4(opub + 256 * 3, o[3]);
      st_rlx4(opub + 256 * 4, o[4]);
    }
    wg_fence();
    turn_wait(turn);
#pragma unroll
    for (int s = 0; s < 5; ++s) {
      wgmma_n80(acc, o[s], dw + (wo_off(0) + 1024 * s >> 4), s);
      if (s == PASS0) turn_pass(pass);
    }
    wg_commit();
    if (PUB34 == 1) {
      st_rlx4(opub + 256 * 3, o[3]);
      st_rlx4(opub + 256 * 4, o[4]);
    }
    TSTAMP(12);
    mbar_wait(bar + 8 * B_WO1, 0);
    sched_fence(P.zero);
#pragma unroll 1
    while (retry<1>(stale<7, 0>(in[0], ep), budget)) {
#pragma unroll
      for (int i = 0; i < 7; ++i) ld_rlx4_stale(in[0][i], src[i] + 2 * BOX * i, in[0][i][0], ep);
    }
    TSTAMP(13);
    fetch(1);
    if (PUB34 == 2) {
      st_rlx4(opub + 256 * 3, o[3]);
      st_rlx4(opub + 256 * 4, o[4]);
    }
#pragma unroll
    for (int s = 0; s < 5; ++s) {
      if (s == FGO_STEP && tid == 128) mbar_arrive(bar + 8 * B_GO);
      wg_fence();
      turn_wait(turn);
#pragma unroll
      for (int i = 0; i < 7; ++i) {
        wgmma_n80(acc, in[s][i], dw + (wo_off(i + 1) + 1024 * s >> 4), 1);
        if (i == PASS_AT - 1) {
          if (s < 4 || p == 0) turn_pass(pass);
          if (s + AHEAD > 1 && s + AHEAD < 5) {
            wg_commit();
            asm volatile("wgmma.wait_group.sync.aligned %0;" ::"n"(AHEAD == 1 ? 3 : 1) : "memory");
            fetch(s + AHEAD);
            wg_fence();
          }
        }
      }
      wg_commit();
    }
    sched_fence(P.zero);
    asm volatile("wgmma.wait_group.sync.aligned 1;" ::: "memory");
    mbar_wait(bar + 8 * B_TAB, 1);
    ld_row(ga, prow + R_GA);
    ldsm4(pb, lane & 1 ? prow + R_P : sb + OFF_PRM + R_ONE);
    ldsm4(pb + 4, lane & 1 ? prow + R_P + 64 : sb + OFF_PRM + R_ONE);
    ldsm2(pb + 8, lane & 1 ? prow + R_P + 128 : sb + OFF_PRM + R_ONE);
    uw = tag(lds1(sb + OFF_KEY + 64), ep);
    const uint32_t bad = stale<28, 0>(in[1], ep) | FORCE_REDO;
    uint32_t redo;
    asm volatile("{.reg .pred p; setp.ne.u32 p, %1, 0; barrier.cta.red.or.aligned.pred p, %2, 128, p; selp.u32 %0, 1, 0, p;}"
                 : "=r"(redo) : "r"(bad & 1u), "r"(turn + (NB_REDO - NB_TURN)) : "memory");
    if (redo) {
      TSTAMP(17);
#pragma unroll 1
      for (int q = 0; q < 40; ++q) {
        const int i = q & 7, s = q >> 3;
        uint32_t a[1][4];
        wg_wait();
        gather<1, 0, 0>(a, lower + (2 * BOX * (i ? i - (i <= g) : g) + 256 * s), ep, budget);
        wg_fence();
        wgmma_n80(acc, a[0], dw + ((i < 4 ? 8 + i : i - 4) * WO + 1024 * s >> 4), q);
        wg_commit();
      }
    }
    wg_wait();
  }
  TSTAMP(18);

  const uint32_t trow = 16 * rb + (lane & 15), xt = sb + (lane >> 4) * 16;
  {
#pragma unroll
    for (int k = 0; k < 20; ++k) xr[k >> 2][k & 3] = fma2(ga[k >> 1], pack2(acc[2 * k], acc[2 * k + 1]), xr[k >> 2][k & 3]);
    float s[4], qlo, qhi;
    row_stats(s, qlo, qhi, xr, pb, gq);
    if (t == gq >> 1) {
      st_rlx4(sdst, u32(s[0]), u32(s[1]), u32(qlo), uw);
      st_rlx4(sdst + 8, u32(s[2]), u32(s[3]), u32(qhi), uw);
    }
    sched_fence(P.zero);
    TSTAMP(19);
#pragma unroll
    for (int s5 = 0; s5 < 5; ++s5) stsm4(xt + trow * 176 + (OFF_X2 + 32 * s5), xr[s5]);
    uint32_t c1[10], sv[10], gb[10], m[4][4];
    ld_row(c1, prow + R_C1);
    ld_row(sv, prow + R_SB);
    ld_row(gb, prow + R_GB);
    if (ST2_GAP) wait_until(clock32() + ST2_GAP);
    gather_lazy<4, 2 * BOX, 4 * BOX, 3>(m, at<16>(P.sc + M_ST2, (16 * j + rank + 8 * (lane & 1)) * BOX + 16 * rb + (lane >> 1)), ep, budget);
    TSTAMP(20);
#pragma unroll
    for (int e = 0; e < 4; ++e) {
      s[e] = (f32(m[0][e]) + f32(m[1][e])) + (f32(m[2][e]) + f32(m[3][e]));
      s[e] += shx(s[e], 1);
    }
    float mean, rstd;
    const uint32_t nw = norm_word(s[0], s[2], mean, rstd), u = u32(rstd * fmaf(-mean, s[3], s[1]));
    const uint32_t key = ((u ^ ((uint32_t)((int)u >> 31) | 0x80000000u)) | 2047u) ^ (256 * j + 32 * rb + (lane & 30) + rank);
    if (key == __reduce_max_sync(0xFFFFFFFFu, key)) sts2(sb + OFF_KEY + 8 * rb, key, nw);
    bar_arrive<NB_KEY, 288>();
    TSTAMP(21);
    const uint32_t n0 = __shfl_sync(0xFFFFFFFFu, nw, 2 * gq), n1 = __shfl_sync(0xFFFFFFFFu, nw, 2 * gq + 16);
    nrm[0] = dup_hi(n0); nrm[1] = dup_hi(n1); nrm[2] = dup_lo(n0); nrm[3] = dup_lo(n1);
#pragma unroll
    for (int k = 0; k < 20; ++k) {
      uint32_t& x = xr[k >> 2][k & 3];
      x = fma2(gb[k >> 1], fma2(fma2(x, nrm[k & 1], nrm[2 + (k & 1)]), c1[k >> 1], sv[k >> 1]), x);
    }
    bar_sync<NB_PUB, 288>();
  }
  TSTAMP(22);

  if (p == 0 && b < N_FFN) {
    uint32_t wf[20][4], m[6][4];
    mbar_wait(bar + 8 * B_FFN, 1);
#pragma unroll
    for (int i = 0; i < 20; ++i)
      ldsm4t(wf[i], sb + OFF_FFN + (lane & 8) * 2560 + (80 * wq + 8 * (lane >> 4) + (lane & 7)) * 64 + (((i & 3) ^ ((lane >> 1) & 3)) << 4) + 1024 * (i >> 2));
    TSTAMP(23);
    const uint32_t far = map_to_cta(sb, 0), dst = far + OFF_ACT + (4 * rank + wq) * 128 + gq * 16, step = map_to_cta(sb, 1) - far;
    gather_lazy<6, 64 * BOX, 8, 0>(m, at<16>(P.sc + M_CAND, (8 * (gq & 6) + 8 * rank + 2 * wq) * BOX + (lane & 7)), ep, budget);
    TSTAMP(24);
    const bool second = m[5][2] > m[4][2];
    const uint32_t wtok = ~__reduce_max_sync(0xFFFFFFFFu, max(m[4][2], m[5][2]));
    float f[4][4];
#pragma unroll
    for (int s = 0; s < 5; ++s) {
      const uint32_t b0 = second ? m[(s & 6) + 1][2 * (s & 1)] : m[s & 6][2 * (s & 1)], b1 = second ? m[(s & 6) + 1][2 * (s & 1) + 1] : m[s & 6][2 * (s & 1) + 1];
#pragma unroll
      for (int mt = 0; mt < 4; ++mt) mma16(f[mt], wf[4 * s + mt], b0, b1, s ? f[mt] : z4);
    }
    if (t == ((wtok >> 8) & 3)) {
      const bool e = wtok & 1;
#pragma unroll
      for (int r = 0; r < 2; ++r)
        asm volatile("st.async.weak.shared::cluster.mbarrier::complete_tx::bytes.v4.f32 [%0], {%1, %2, %3, %4}, [%5];"
                     ::"r"(dst + r * step), "f"(e ? f[2 * r][1] : f[2 * r][0]), "f"(e ? f[2 * r][3] : f[2 * r][2]),
                       "f"(e ? f[2 * r + 1][1] : f[2 * r + 1][0]), "f"(e ? f[2 * r + 1][3] : f[2 * r + 1][2]), "r"(far + r * step + (OFF_BAR + 8 * B_ACT)) : "memory");
    }
    __syncwarp();
    if (warp == 0) {
      sts1(sb + OFF_KEY + 80, ~wtok);
      if (b < 80) bar_arrive<NB_WIN, 64>();
    }
    TSTAMP(25);
  }
#pragma unroll
  for (int s5 = 0; s5 < 5; ++s5) stsm4(xt + trow * 160 + (OFF_OUT + 32 * s5), xr[s5]);
  asm volatile("fence.proxy.async.shared::cta;" ::: "memory");
  asm volatile("bar.arrive %0, 160;" ::"r"(turn + (NB_OUT - NB_TURN)) : "memory");
  if (p == 1 && b < N_FFN) {
    const uint32_t kr = ((lane & 7) >> 1) + 4 * (lane >> 4) + 8 * (lane & 1);
    uint32_t wd[10][4];
    mbar_wait(bar + 8 * B_XS, 0);
#pragma unroll
    for (int i = 0; i < 10; ++i) ldsm4t(wd[i], sb + OFF_FFN + 40960 + kr * 128 + (((2 * wq + ((lane >> 3) & 1)) ^ (kr & 7)) << 4) + 2048 * i);
    TSTAMP(23);
    uint4* const ydst = at<16>(P.sc + M_YP, ((b & ~3) + wq) * BOX + 4 * (gq & 6) + 2 * (b & 3) + (gq & 1));
    mbar_wait(bar + 8 * B_ACT, 1);
    TSTAMP(24);
    float v[8];
#pragma unroll
    for (int i = 0; i < 8; ++i) v[i] = f32(lds1(sb + OFF_ACT + 128 * i + 4 * lane));
    const float gu = bf_round(((v[0] + v[1]) + (v[2] + v[3])) + ((v[4] + v[5]) + (v[6] + v[7])));
    const float a = bf_round(gu * sigmoid(gu)) * shx(gu, 1);
    const uint32_t aw = pack2(a, shx(a, 2));
    const uint32_t b0 = __shfl_sync(0xFFFFFFFFu, aw, 4 * t), b1 = __shfl_sync(0xFFFFFFFFu, aw, 4 * t + 16);
    const bool odd = gq & 1;
    float y[5][4];
#pragma unroll
    for (int q = 0; q < 5; ++q) mma16(y[q], wd[2 * q], odd ? 0u : b0, odd ? 0u : b1, z4);
#pragma unroll
    for (int q = 0; q < 5; ++q) mma16(y[q], wd[2 * q + 1], odd ? b0 : 0u, odd ? b1 : 0u, y[q]);
    uint32_t w[4];
#pragma unroll
    for (int e = 0; e < 4; ++e) w[e] = u32(t & 2 ? (t & 1 ? y[3][e] : y[2][e]) : (t & 1 ? y[1][e] : y[0][e]));
    st_rlx4(ydst + 32 * t, tag(w[0], ep), w[1], w[2], w[3]);
    if (t == 0) st_rlx4(ydst + 128, tag(u32(y[4][0]), ep), u32(y[4][1]), u32(y[4][2]), u32(y[4][3]));
    __syncwarp();
    if (warp == 4 && b < 80) bar_arrive<NB_YP, 64>();
    TSTAMP(25);
  }
}

__global__ void __cluster_dims__(2, 1, 1) __launch_bounds__(384, 1) fused_block_kernel(const __grid_constant__ Params P) {
  extern __shared__ __align__(1024) uint8_t sm[];
  const uint32_t sb = (uint32_t)__cvta_generic_to_shared(sm), t0 = clock32();
  const int tid = threadIdx.x, lane = tid & 31;
  uint32_t key = blockIdx.x;
  asm("mov.u32 %0, %%smid;" : "=r"(key));
  const __nv_bfloat16* wmod = (&P.wmod)[tid >> 9];
  asm volatile("" : "+l"(wmod));
  const int warp = __shfl_sync(0xFFFFFFFFu, tid >> 5, 0), c = key >> 1, rank = blockIdx.x & 1;
  const uint32_t bar = sb + OFF_BAR;
  const auto role = [&]() {
    const int q7 = ((c - 32) * 37) >> 8;
    return 2 * pick(c < 32, 8 * (c & 7) + (c >> 3), pick(c < 60, 8 * c - 55 * q7 - 244, c - 58)) + rank;
  };
  const bool spare = BY_SM && (c >> 1) == 30;
  int budget = SPIN_LIMIT, b;
  uint32_t e0 = 0;
  if (warp == 11) {
    if (elect_one()) {
#pragma unroll
      for (int i = 0; i < 12; ++i) mbar_init(bar + 8 * i, i == B_TAB ? 96 : i == B_HALO ? 8 : (i >> 2) == 1 ? 16 : 1);
      asm volatile("fence.mbarrier_init.release.cluster;" ::: "memory");
    }
    __syncwarp();
    asm volatile("barrier.cluster.arrive.relaxed.aligned;" ::: "memory");
    b = role();
    if (spare) {
      wait_until(t0 + 4000);
      return;
    }
    TSTAMP(27);
    const int g = (b >> 1) & 7;
    if (elect_one()) {
      mbar_expect_tx(bar + 8 * B_FULL, STAGE);
      tma2(sb, &P.xa, bar + 8 * B_FULL, 640 * rank, 128 * (b >> 4));
    }
    asm volatile("barrier.cluster.wait.aligned;" ::: "memory");
    if (elect_one()) {
      tma3_both(sb + STAGE_A + rank * (STAGE_B0 / 2), &P.w0, bar + 8 * B_FULL, 80 * g, 32 * rank, 0);
      tma3_both(sb + STAGE_A + STAGE_B0 + rank * (STAGE_B1 / 2), &P.w1, bar + 8 * B_FULL, 80 * g + 64, 32 * rank, 0);
    }
    TSTAMP(28);
    st_rlx1(at<4>(P.sc + M_ST1, b * (4 * BOX) + lane), 0u);
    __syncwarp();
    if (lane == 0) mbar_arrive(bar + 8 * B_XS);
  } else {
    asm volatile("barrier.cluster.arrive.relaxed.aligned;" ::: "memory");
    const int u = (c & 48) + 2 * (c & 7) + ((c >> 3) & 1) - (c & 32 ? c & 7 : 0), kb = 2 * u + rank;
    const bool gemv = warp < 10 && c < 40;
    uint32_t cv = 0;
    if (gemv) {
      const __nv_bfloat16* src = at<16>(wmod, (320 * rank + (tid >> 2)) * 480 + 4 * u + (tid & 3));
      const uint32_t dst = sb + 3 * STAGE + 16 * (tid ^ ((tid >> 3) & 3));
#pragma unroll
      for (int i = 0; i < 4; ++i)
        asm volatile("cp.async.cg.shared.global.L2::128B [%0], [%1], 16;" ::"r"(dst + 5120 * i), "l"(src + i * 80 * 3840) : "memory");
    } else if (warp == 10 && elect_one()) {
      asm volatile("prefetch.tensormap [%0];" ::"l"(&P.xa) : "memory");
      asm volatile("prefetch.tensormap [%0];" ::"l"(&P.w0) : "memory");
      asm volatile("prefetch.tensormap [%0];" ::"l"(&P.w1) : "memory");
    }
    TSTAMP(26);
    asm volatile("barrier.cluster.wait.aligned;" ::: "memory");
    if (spare) return;
    if (gemv) asm volatile("ld.global.nc.u16 %0, [%1];" : "=r"(cv) : "l"(at<2>(P.c, 320 * rank + 10 * (tid & 24) + ((tid >> 2) & ~7) + (tid & 7))));
    b = role();
    uint4* const box = P.sc + b * BOX;
    e0 = ld_rlx1(at<4>(box + M_EPOCH, lane));
    asm volatile("cp.async.commit_group;" ::: "memory");
    if (warp < 8) {
      const __nv_bfloat16* src = at<16>(P.x, (16 * b + (tid >> 4)) * 80 + (tid & 15));
      wait_until(t0 + XS_AT);
#pragma unroll
      for (int i = 0; i < 5; ++i)
        asm volatile("cp.async.cg.shared.global [%0], [%1], 16;" ::"r"(sb + OFF_XS + 4096 * i + 16 * tid), "l"(src + 128 * i) : "memory");
    }
    if (warp == 10) {
      uint4* const dst = at<16>(P.sc, kb * BOX + lane);
      if (c < 40) st_rlx4(dst, 0u, 0u, 0u, 0u);
      if (lane == 0) mbar_expect_tx(bar + 8 * B_GO, c < 40 ? 1280 : 0);
      TALIGN(0);
      if (c < 40) {
        const uint32_t ep = next_epoch(e0);
        mbar_wait(bar + 8 * B_GO, 0);
        TSTAMP(1);
        float v[10];
#pragma unroll
        for (int i = 0; i < 10; ++i) v[i] = f32(lds1(sb + OFF_RED + 128 * i + 4 * lane));
        float s = ((v[0] + v[1]) + (v[2] + v[3])) + ((v[4] + v[5]) + (v[6] + v[7])) + (v[8] + v[9]);
        s += shx(s, 16);
        const uint32_t w = fma2(pack2(s, shx(s, 1)), 0x3F803F80u, kb < 40 ? 0u : 0x3F803F80u);
        st_rlx4(dst, __shfl_sync(0xFFFFFFFFu, w, 2 * (lane & 3)), __shfl_sync(0xFFFFFFFFu, w, 2 * (lane & 3) + 8), ep, ep);
        TSTAMP(2);
      }
    } else if (gemv) {
      const float x = bf_lo(cv), s = x * sigmoid(x);
      const uint32_t sw = pack2(s, shx(s, 1));
      uint32_t bw[4], a[4][4];
#pragma unroll
      for (int i = 0; i < 4; ++i) bw[i] = __shfl_sync(0xFFFFFFFFu, sw, 8 * i + 2 * (lane & 3));
      const uint32_t far = map_to_cta(sb, (lane >> 1) & 1), dst = far + OFF_RED + 128 * warp + 64 * rank + 32 * (lane & 1) + (lane & 28);
      const uint32_t la = sb + 3 * STAGE + 512 * warp + (lane >> 4) * 5120 + (lane & 7) * 64 + ((((lane >> 3) & 1) ^ ((lane >> 1) & 3)) << 4);
      sched_fence(P.zero);
      asm volatile("cp.async.wait_group 0;" ::: "memory");
      __syncwarp();
      TSTAMP(28);
#pragma unroll
      for (int i = 0; i < 4; ++i) ldsm4t(a[i], (la ^ (32 * (i & 1))) + (i >> 1) * 10240);
      float d[2][4];
      const float z4[4] = {0.f, 0.f, 0.f, 0.f};
#pragma unroll
      for (int i = 0; i < 4; ++i) mma16(d[i & 1], a[i], bw[i & 2], bw[(i & 2) + 1], i < 2 ? z4 : d[i & 1]);
      const float v = lane & 2 ? (lane & 1 ? d[1][2] : d[1][0]) : (lane & 1 ? d[0][2] : d[0][0]);
      asm volatile("st.async.weak.shared::cluster.mbarrier::complete_tx::bytes.f32 [%0], %1, [%2];" ::"r"(dst), "f"(v), "r"(far + OFF_BAR + 8 * B_GO) : "memory");
      TSTAMP(1);
    }
  }
  if (warp >= 8) {
    asm volatile("setmaxnreg.dec.sync.aligned.u32 56;");
    if (warp == 11) {
      wait_until(t0 + S_GAP);
      run_producer(P, sm, sb, b, t0);
    } else {
      run_helper(P, sm, sb, b, warp - 8, next_epoch(e0), budget, t0 + POLL_AT);
    }
    TDUMP();
  } else {
    run_consumer(P, sm, sb, b, warp, next_epoch(e0), budget);
    TDUMP();
  }
}

typedef CUresult (*EncodeFn)(CUtensorMap*, CUtensorMapDataType, cuuint32_t, void*, const cuuint64_t*, const cuuint64_t*, const cuuint32_t*,
                             const cuuint32_t*, CUtensorMapInterleave, CUtensorMapSwizzle, CUtensorMapL2promotion, CUtensorMapFloatOOBfill);

void encode(EncodeFn fn, CUtensorMap* m, const void* base, int rank, const cuuint64_t* dims, const cuuint64_t* strides, const cuuint32_t* box,
            CUtensorMapSwizzle sw) {
  const cuuint32_t es[3] = {1, 1, 1};
  fn(m, CU_TENSOR_MAP_DATA_TYPE_BFLOAT16, rank, const_cast<void*>(base), dims, strides, box, es, CU_TENSOR_MAP_INTERLEAVE_NONE, sw,
     CU_TENSOR_MAP_L2_PROMOTION_L2_128B, CU_TENSOR_MAP_FLOAT_OOB_FILL_NONE);
}

}

extern "C" void kernel_launch(void* const* d_in, const int* in_sizes, int n_in, void* d_out, int out_size) {
  (void)in_sizes; (void)n_in; (void)out_size;
  static EncodeFn fn = nullptr;
  static void* scratch = nullptr;
  if (!fn) {
    void* f = nullptr;
    cudaDriverEntryPointQueryResult q;
    cudaGetDriverEntryPoint("cuTensorMapEncodeTiled", &f, cudaEnableDefault, &q);
    fn = (EncodeFn)f;
    cudaFuncSetAttribute(fused_block_kernel, cudaFuncAttributeMaxDynamicSharedMemorySize, SMEM_BYTES);
    cudaGetSymbolAddress(&scratch, g_scratch);
  }
  Params P;
  P.sc = (uint4*)scratch;
  P.zero = 0;
  const cuuint64_t xd[2] = {1280, 1024}, xs[1] = {2560};
  const cuuint32_t xb[2] = {64, 128};
  encode(fn, &P.xa, d_in[0], 2, xd, xs, xb, CU_TENSOR_MAP_SWIZZLE_128B);
  const cuuint32_t ob[2] = {80, 16};
  encode(fn, &P.om, d_out, 2, xd, xs, ob, CU_TENSOR_MAP_SWIZZLE_NONE);
  const cuuint64_t wd3[3] = {640, 640, 3}, ws3[2] = {3840, 1280};
  const cuuint32_t w0b[3] = {64, 32, 3}, w1b[3] = {16, 32, 3};
  encode(fn, &P.w0, d_in[1], 3, wd3, ws3, w0b, CU_TENSOR_MAP_SWIZZLE_128B);
  encode(fn, &P.w1, d_in[1], 3, wd3, ws3, w1b, CU_TENSOR_MAP_SWIZZLE_32B);
  const cuuint64_t md[2] = {3840, 640}, ms[1] = {7680};
  const cuuint32_t mb[2] = {80, 160};
  encode(fn, &P.wm, d_in[9], 2, md, ms, mb, CU_TENSOR_MAP_SWIZZLE_NONE);
  const cuuint64_t od3[3] = {608, 640, 2}, os3[2] = {1280, 64}, od2[2] = {640, 640}, os2[1] = {1280};
  const cuuint32_t oab[3] = {32, 80, 2}, obb[2] = {16, 80};
  encode(fn, &P.woa, d_in[2], 3, od3, os3, oab, CU_TENSOR_MAP_SWIZZLE_64B);
  encode(fn, &P.wob, d_in[2], 2, od2, os2, obb, CU_TENSOR_MAP_SWIZZLE_64B);
  const cuuint64_t gd[3] = {1728, 160, 4}, gs[2] = {3456, 160 * 3456}, dd[3] = {64, 1728, 10}, ds[2] = {1280, 128};
  const cuuint32_t gb[3] = {32, 160, 1}, db[3] = {64, 16, 5};
  encode(fn, &P.wg, d_in[5], 3, gd, gs, gb, CU_TENSOR_MAP_SWIZZLE_64B);
  encode(fn, &P.wu, d_in[6], 3, gd, gs, gb, CU_TENSOR_MAP_SWIZZLE_64B);
  encode(fn, &P.wd, d_in[7], 3, dd, ds, db, CU_TENSOR_MAP_SWIZZLE_128B);
  P.x = (const __nv_bfloat16*)d_in[0];
  P.wqkv = (const __nv_bfloat16*)d_in[1];
  P.wr = (const __nv_bfloat16*)d_in[4];
  P.wo = (const __nv_bfloat16*)d_in[2];
  P.wgate = (const __nv_bfloat16*)d_in[5];
  P.wup = (const __nv_bfloat16*)d_in[6];
  P.wdown = (const __nv_bfloat16*)d_in[7];
  P.c = (const __nv_bfloat16*)d_in[8];
  P.wmod = (const __nv_bfloat16*)d_in[9];
  P.out = (__nv_bfloat16*)d_out;
  fused_block_kernel<<<BY_SM ? 132 : 128, 384, SMEM_BYTES>>>(P);
}
```

```cpp
#include <cuda_runtime.h>
#include <cuda.h>
#include <cuda_bf16.h>
#include <stdint.h>

namespace {

constexpr int STAGE_A = 16384, STAGE_B0 = 24576, STAGE_B1 = 6144, STAGE = STAGE_A + STAGE_B0 + STAGE_B1;
constexpr int WO = 15360;
constexpr int OFF_FFN = 4 * WO, OFF_LM = 2 * STAGE, OFF_X2 = 4 * STAGE, OFF_OUT = 0;
constexpr int OFF_H = 4 * STAGE, OFF_L = OFF_H + 9 * 2560, OFF_XS = OFF_H, OFF_RED = OFF_L, OFF_SINK = OFF_L + 10240;
constexpr int OFF_C1 = 225280, OFF_ACT = OFF_C1, OFF_ROWS = OFF_C1 + 1024, OFF_PRM = OFF_C1 + 2560, OFF_SILU = OFF_PRM + 1600;
constexpr int OFF_KEY = OFF_SILU + 320, OFF_BAR = OFF_KEY + 128, OFF_TIME = OFF_BAR + 256, SMEM_BYTES = OFF_TIME + 1536;
static_assert(OFF_H % 512 == 0, "lane bits of the halo address");
static_assert(SMEM_BYTES <= 232448 && OFF_BAR % 64 == 0, "smem");
enum { R_GA = 0, R_SB = 160, R_C1 = 320, R_GB = 480, R_FIN = 640, R_P = 800 + R_C1, R_ONE = 704 };

enum { B_FULL = 0, B_EMPTY = 4, B_HALO = 8, B_TAB = 9, B_GO = 10, B_XS = 11, B_ACT = B_FULL, B_FFN = B_FULL + 1, B_WO0 = B_FULL + 2, B_WO1 = B_FULL + 3 };
enum { NB_PV = 1, NB_TURN = 2, NB_KEY = 4, NB_REDO = 5, NB_HELP = 6, NB_HALO = 7, NB_PUB = 8, NB_GO = 9, NB_LM = 10, NB_OUT = 11, NB_WIN = 13, NB_YP = 14 };

enum { M_EARLY = 0, M_ST1 = 32, M_EPOCH = 40, M_HALO = 48, M_ST2 = 208, M_CAND = 336, M_LATE = 368, M_YP = 400, M_O = 560, BOX = 1840 };
constexpr int TABLES = 128 * BOX;
__device__ uint4 g_scratch[TABLES + 8 * 320];

constexpr int N_FFN = 108;
#define BY_SM 1
#define HI_FIRST 0
#define HALO_FENCE 1
#define AHEAD 1
#define FORCE_REDO 0
#define FFN_EARLY 0
#define DOWN_GAP 1900
#define CAND_GAP 0
#define NAP 20
#define XS_AT 900
#define S_GAP 1300
#define POLL_AT 4000
#define WPF_AT 4500
#define LMPF_AT 4
#define TOUCH_AT 1000
#define TOUCH_GAP 1100
#define HALO_GAP 400
#define LATE_GAP 800
#define FGO_STEP 4
#define FFN_GAP 0
#define ST2_GAP 0
#define OUT_AT 400
#define OUT_GAP 0
#define YP_GAP 250
#define PASS1 5
#define PASS0 2
#define PASS_AT 3
constexpr int SPIN_LIMIT = 1 << 16;

struct Params {
  const __nv_bfloat16 *wmod, *c, *x;
  uint4* sc;
  uint32_t zero;
  const __nv_bfloat16 *wqkv, *wr, *wo, *wgate, *wup, *wdown;
  __nv_bfloat16* out;
  CUtensorMap xa, w0, w1, wm0, wm1, woa, wob, wg, wu, wd, om;
};

__device__ __forceinline__ uint32_t clock32() {
  uint32_t c;
  asm volatile("mov.u32 %0, %%clock;" : "=r"(c));
  return c;
}
#define TSTAMP(i) do { } while (0)
#define TDUMP() do { } while (0)
#define TALIGN(k) do { } while (0)

__device__ __forceinline__ void mbar_init(uint32_t b, uint32_t c) { asm volatile("mbarrier.init.shared::cta.b64 [%0], %1;" ::"r"(b), "r"(c) : "memory"); }
__device__ __forceinline__ void mbar_expect_tx(uint32_t b, uint32_t n) { asm volatile("mbarrier.arrive.expect_tx.shared::cta.b64 _, [%0], %1;" ::"r"(b), "r"(n) : "memory"); }
__device__ __forceinline__ void mbar_arrive(uint32_t b) { asm volatile("mbarrier.arrive.shared::cta.b64 _, [%0];" ::"r"(b) : "memory"); }
__device__ __forceinline__ uint32_t map_to_cta(uint32_t a, uint32_t rank) {
  uint32_t r;
  asm("mapa.shared::cluster.u32 %0, %1, %2;" : "=r"(r) : "r"(a), "r"(rank));
  return r;
}
__device__ __forceinline__ void mbar_arrive_cluster(uint32_t b) { asm volatile("mbarrier.arrive.shared::cluster.b64 _, [%0];" ::"r"(b) : "memory"); }
__device__ __forceinline__ void mbar_wait(uint32_t b, uint32_t ph) {
  asm volatile("{.reg .pred p;\n"
               "RETRY: mbarrier.try_wait.parity.shared::cta.b64 p, [%0], %1;\n"
               "@!p bra RETRY;}" ::"r"(b), "r"(ph) : "memory");
}
__device__ __forceinline__ bool elect_one() {
  uint32_t r;
  asm volatile("{.reg .pred p; elect.sync _|p, 0xFFFFFFFF; selp.u32 %0, 1, 0, p;}" : "=r"(r));
  return r;
}
template <int ID, int N> __device__ __forceinline__ void bar_sync() { asm volatile("bar.sync %0, %1;" ::"n"(ID), "n"(N) : "memory"); }
template <int ID, int N> __device__ __forceinline__ void bar_arrive() { asm volatile("bar.arrive %0, %1;" ::"n"(ID), "n"(N) : "memory"); }
__device__ __forceinline__ void turn_wait(uint32_t id) { asm volatile("bar.sync %0, 256;" ::"r"(id) : "memory"); }
__device__ __forceinline__ void turn_pass(uint32_t id) { asm volatile("bar.arrive %0, 256;" ::"r"(id) : "memory"); }
__device__ __forceinline__ void tma2(uint32_t dst, const CUtensorMap* m, uint32_t bar, int c0, int c1) {
  asm volatile("cp.async.bulk.tensor.2d.shared::cluster.global.mbarrier::complete_tx::bytes [%0], [%1, {%3, %4}], [%2];" ::"r"(dst), "l"(m), "r"(bar), "r"(c0), "r"(c1) : "memory");
}
__device__ __forceinline__ void tma3(uint32_t dst, const CUtensorMap* m, uint32_t bar, int c0, int c1, int c2) {
  asm volatile("cp.async.bulk.tensor.3d.shared::cluster.global.mbarrier::complete_tx::bytes [%0], [%1, {%3, %4, %5}], [%2];" ::"r"(dst), "l"(m), "r"(bar), "r"(c0), "r"(c1), "r"(c2) : "memory");
}
__device__ __forceinline__ void tma2_both(uint32_t dst, const CUtensorMap* m, uint32_t bar, int c0, int c1) {
  asm volatile("cp.async.bulk.tensor.2d.shared::cluster.global.mbarrier::complete_tx::bytes.multicast::cluster [%0], [%1, {%3, %4}], [%2], %5;"
               ::"r"(dst), "l"(m), "r"(bar), "r"(c0), "r"(c1), "h"((uint16_t)3) : "memory");
}
__device__ __forceinline__ void tma3_both(uint32_t dst, const CUtensorMap* m, uint32_t bar, int c0, int c1, int c2) {
  asm volatile("cp.async.bulk.tensor.3d.shared::cluster.global.mbarrier::complete_tx::bytes.multicast::cluster [%0], [%1, {%3, %4, %5}], [%2], %6;"
               ::"r"(dst), "l"(m), "r"(bar), "r"(c0), "r"(c1), "r"(c2), "h"((uint16_t)3) : "memory");
}
__device__ __forceinline__ void bulk_prefetch(const void* src, uint32_t bytes) {
  asm volatile("cp.async.bulk.prefetch.L2.global [%0], %1;" ::"l"(src), "r"(bytes) : "memory");
}
__device__ __forceinline__ void wg_fence() { asm volatile("wgmma.fence.sync.aligned;" ::: "memory"); }
__device__ __forceinline__ void wg_commit() { asm volatile("wgmma.commit_group.sync.aligned;" ::: "memory"); }
__device__ __forceinline__ void wg_wait() { asm volatile("wgmma.wait_group.sync.aligned 0;" ::: "memory"); }
__device__ __forceinline__ uint64_t make_desc(uint32_t addr, uint32_t lbo, uint32_t sbo, uint32_t mode) {
  return (uint64_t)((addr & 0x3FFFF) >> 4) | ((uint64_t)(lbo >> 4) << 16) | ((uint64_t)(sbo >> 4) << 32) | ((uint64_t)mode << 62);
}
__device__ __forceinline__ void ldsm4(uint32_t& r0, uint32_t& r1, uint32_t& r2, uint32_t& r3, uint32_t a) {
  asm volatile("ldmatrix.sync.aligned.m8n8.x4.shared.b16 {%0, %1, %2, %3}, [%4];" : "=r"(r0), "=r"(r1), "=r"(r2), "=r"(r3) : "r"(a) : "memory");
}
__device__ __forceinline__ void ldsm4(uint32_t* r, uint32_t a) { ldsm4(r[0], r[1], r[2], r[3], a); }
__device__ __forceinline__ void ldsm2(uint32_t* r, uint32_t a) {
  asm volatile("ldmatrix.sync.aligned.m8n8.x2.shared.b16 {%0, %1}, [%2];" : "=r"(r[0]), "=r"(r[1]) : "r"(a) : "memory");
}
__device__ __forceinline__ void ldsm4t(uint32_t* r, uint32_t a) {
  asm volatile("ldmatrix.sync.aligned.m8n8.x4.trans.shared.b16 {%0, %1, %2, %3}, [%4];" : "=r"(r[0]), "=r"(r[1]), "=r"(r[2]), "=r"(r[3]) : "r"(a) : "memory");
}
__device__ __forceinline__ void ldsm2t(uint32_t* r, uint32_t a) {
  asm volatile("ldmatrix.sync.aligned.m8n8.x2.trans.shared.b16 {%0, %1}, [%2];" : "=r"(r[0]), "=r"(r[1]) : "r"(a) : "memory");
}
__device__ __forceinline__ void ld_row(uint32_t (&r)[10], uint32_t a) {
  ldsm4(r, a);
  ldsm4(r + 4, a + 64);
  ldsm2(r + 8, a + 128);
}
__device__ __forceinline__ void stsm4(uint32_t a, const uint32_t* r) {
  asm volatile("stmatrix.sync.aligned.m8n8.x4.shared.b16 [%0], {%1, %2, %3, %4};" ::"r"(a), "r"(r[0]), "r"(r[1]), "r"(r[2]), "r"(r[3]) : "memory");
}
__device__ __forceinline__ void stsm2(uint32_t a, const uint32_t* r) {
  asm volatile("stmatrix.sync.aligned.m8n8.x2.shared.b16 [%0], {%1, %2};" ::"r"(a), "r"(r[0]), "r"(r[1]) : "memory");
}
__device__ __forceinline__ void lds4(uint32_t* r, uint32_t a) {
  asm volatile("ld.shared.v4.u32 {%0, %1, %2, %3}, [%4];" : "=r"(r[0]), "=r"(r[1]), "=r"(r[2]), "=r"(r[3]) : "r"(a) : "memory");
}
__device__ __forceinline__ uint32_t lds1(uint32_t a) {
  uint32_t v;
  asm volatile("ld.shared.u32 %0, [%1];" : "=r"(v) : "r"(a) : "memory");
  return v;
}
__device__ __forceinline__ void sts1(uint32_t a, uint32_t v) { asm volatile("st.shared.u32 [%0], %1;" ::"r"(a), "r"(v) : "memory"); }
__device__ __forceinline__ void sts2(uint32_t a, uint32_t v0, uint32_t v1) { asm volatile("st.shared.v2.u32 [%0], {%1, %2};" ::"r"(a), "r"(v0), "r"(v1) : "memory"); }
__device__ __forceinline__ void mma16(float (&d)[4], uint32_t a0, uint32_t a1, uint32_t a2, uint32_t a3, uint32_t b0, uint32_t b1, const float* c) {
  asm volatile("mma.sync.aligned.m16n8k16.row.col.f32.bf16.bf16.f32 {%0, %1, %2, %3}, {%4, %5, %6, %7}, {%8, %9}, {%10, %11, %12, %13};"
               : "=f"(d[0]), "=f"(d[1]), "=f"(d[2]), "=f"(d[3])
               : "r"(a0), "r"(a1), "r"(a2), "r"(a3), "r"(b0), "r"(b1), "f"(c[0]), "f"(c[1]), "f"(c[2]), "f"(c[3]));
}
__device__ __forceinline__ void mma16(float (&d)[4], const uint32_t* a, uint32_t b0, uint32_t b1, const float* c) { mma16(d, a[0], a[1], a[2], a[3], b0, b1, c); }
__device__ __forceinline__ void mma8(float (&d)[4], uint32_t a0, uint32_t a1, uint32_t b0, const float* c) {
  asm volatile("mma.sync.aligned.m16n8k8.row.col.f32.bf16.bf16.f32 {%0, %1, %2, %3}, {%4, %5}, {%6}, {%7, %8, %9, %10};"
               : "=f"(d[0]), "=f"(d[1]), "=f"(d[2]), "=f"(d[3]) : "r"(a0), "r"(a1), "r"(b0), "f"(c[0]), "f"(c[1]), "f"(c[2]), "f"(c[3]));
}
__device__ __forceinline__ uint32_t pack2(float lo, float hi) {
  uint32_t r;
  asm volatile("cvt.rn.bf16x2.f32 %0, %1, %2;" : "=r"(r) : "f"(hi), "f"(lo));
  return r;
}
__device__ __forceinline__ float bf_lo(uint32_t w) { return __uint_as_float(w << 16); }
__device__ __forceinline__ float bf_hi(uint32_t w) { return __uint_as_float(w & 0xFFFF0000u); }
__device__ __forceinline__ float bf_round(float v) { return __uint_as_float(pack2(0.f, v)); }
__device__ __forceinline__ uint32_t fma2(uint32_t a, uint32_t b, uint32_t c) {
  uint32_t r;
  asm("fma.rn.bf16x2 %0, %1, %2, %3;" : "=r"(r) : "r"(a), "r"(b), "r"(c));
  return r;
}
__device__ __forceinline__ void acc2(uint32_t& c, uint32_t a, uint32_t b) { asm("fma.rn.bf16x2 %0, %1, %2, %0;" : "+r"(c) : "r"(a), "r"(b)); }
__device__ __forceinline__ float ex2(float v) {
  float r;
  asm("ex2.approx.ftz.f32 %0, %1;" : "=f"(r) : "f"(v));
  return r;
}
__device__ __forceinline__ float rcp(float v) {
  float r;
  asm("rcp.approx.ftz.f32 %0, %1;" : "=f"(r) : "f"(v));
  return r;
}
__device__ __forceinline__ float rsq(float v) {
  float r;
  asm("rsqrt.approx.ftz.f32 %0, %1;" : "=f"(r) : "f"(v));
  return r;
}
__device__ __forceinline__ float sigmoid(float v) { return rcp(1.f + ex2(v * -1.4426950408889634f)); }
__device__ __forceinline__ float f32(uint32_t v) { return __uint_as_float(v); }
__device__ __forceinline__ uint32_t u32(float v) { return __float_as_uint(v); }
__device__ __forceinline__ void ld_rlx4(uint32_t* v, const void* p) {
  asm volatile("{.reg .b128 q; ld.relaxed.gpu.global.b128 q, [%4]; mov.b128 {%0, %1, %2, %3}, q;}" : "=r"(v[0]), "=r"(v[1]), "=r"(v[2]), "=r"(v[3]) : "l"(p) : "memory");
}
__device__ __forceinline__ void ld_rlx2(uint32_t* v, const void* p) {
  asm volatile("{.reg .b64 q; ld.relaxed.gpu.global.b64 q, [%2]; mov.b64 {%0, %1}, q;}" : "=r"(v[0]), "=r"(v[1]) : "l"(p) : "memory");
}
__device__ __forceinline__ uint32_t ld_rlx1(const void* p) {
  uint32_t v;
  asm volatile("ld.relaxed.gpu.global.u32 %0, [%1];" : "=r"(v) : "l"(p) : "memory");
  return v;
}
__device__ __forceinline__ void st_rlx4(void* p, uint32_t a, uint32_t b, uint32_t c, uint32_t d) {
  asm volatile("{.reg .b128 q; mov.b128 q, {%1, %2, %3, %4}; st.relaxed.gpu.global.b128 [%0], q;}" ::"l"(p), "r"(a), "r"(b), "r"(c), "r"(d) : "memory");
}
__device__ __forceinline__ void st_rlx4(void* p, const uint32_t* v) { st_rlx4(p, v[0], v[1], v[2], v[3]); }
__device__ __forceinline__ void st_rlx2(void* p, uint32_t a, uint32_t b) { asm volatile("{.reg .b64 q; mov.b64 q, {%1, %2}; st.relaxed.gpu.global.b64 [%0], q;}" ::"l"(p), "r"(a), "r"(b) : "memory"); }
__device__ __forceinline__ void st_rlx1(void* p, uint32_t v) { asm volatile("st.relaxed.gpu.global.u32 [%0], %1;" ::"l"(p), "r"(v) : "memory"); }
template <int LUT> __device__ __forceinline__ uint32_t lop3(uint32_t a, uint32_t b, uint32_t c) {
  uint32_t r;
  asm volatile("lop3.b32 %0, %1, %2, %3, %4;" : "=r"(r) : "r"(a), "r"(b), "r"(c), "n"(LUT));
  return r;
}
__device__ __forceinline__ uint32_t tag(uint32_t w, uint32_t ep) { return lop3<0xD8>(w, ep, 1u); }
__device__ __forceinline__ uint32_t neq2(uint32_t a, uint32_t b, uint32_t e) { return lop3<0x7E>(a, b, e); }
__device__ __forceinline__ uint32_t next_epoch(uint32_t e) {
  asm volatile("add.u32 %0, %0, 1;" : "+r"(e));
  return e;
}
__device__ __forceinline__ void sched_fence(uint32_t zero) {
  asm volatile("{.reg .pred p; setp.ne.u32 p, %0, 0;\nSPIN: pmevent 0; @p bra.uni SPIN;}" ::"r"(zero) : "memory");
}
__device__ __forceinline__ int pick(bool c, int a, int b) {
  int r;
  asm("{.reg .pred p; setp.ne.u32 p, %1, 0; selp.b32 %0, %2, %3, p;}" : "=r"(r) : "r"((uint32_t)c), "r"(a), "r"(b));
  return r;
}
__device__ __forceinline__ uint32_t keep(uint32_t v) { return __shfl_xor_sync(0xFFFFFFFFu, v, 2); }
__device__ __forceinline__ void wait_until(uint32_t t) {
  while ((int)(clock32() - t) < 0) {
    asm volatile("nanosleep.u32 %0;" ::"n"(NAP));
  }
}
__device__ __forceinline__ float shx(float v, int o) { return __shfl_xor_sync(0xFFFFFFFFu, v, o); }
template <int SCALE, class T> __device__ __forceinline__ T* at(T* base, uint32_t i) {
  T* r;
  asm volatile("mad.wide.u32 %0, %1, %2, %3;" : "=l"(r) : "r"(i), "n"(SCALE), "l"(base));
  return r;
}
template <uint32_t MASK> __device__ __forceinline__ bool retry(uint32_t bad, int& budget) {
  uint32_t r;
  asm volatile("{.reg .pred p, q; .reg .b32 t; add.s32 %1, %1, -1; setp.gt.s32 q, %1, 0; and.b32 t, %2, %3; setp.ne.u32 p, t, 0;\n"
               "vote.sync.any.pred p, p, 0xFFFFFFFF; and.pred p, p, q; selp.u32 %0, 1, 0, p;}" : "=r"(r), "+r"(budget) : "r"(bad), "n"(MASK));
  return r;
}
template <int N, int W> __device__ __forceinline__ uint32_t stale(const uint32_t (*v)[4], uint32_t ep) {
  uint32_t bad = neq2(v[0][W], v[N > 1][W], ep);
#pragma unroll
  for (int i = 2; i < N; i += 2) bad |= neq2(v[i][W], v[i + 1 < N ? i + 1 : i][W], ep);
  return bad;
}
__device__ __forceinline__ void ld_rlx4_stale(uint32_t* v, const void* p, uint32_t w, uint32_t ep) {
  asm volatile("{.reg .b128 q; .reg .pred p; .reg .b32 t; lop3.b32 t, %5, %6, 1, 0x28; setp.ne.u32 p, t, 0; mov.b128 q, {%0, %1, %2, %3};\n"
               "@p ld.relaxed.gpu.global.b128 q, [%4]; mov.b128 {%0, %1, %2, %3}, q;}"
               : "+r"(v[0]), "+r"(v[1]), "+r"(v[2]), "+r"(v[3]) : "l"(p), "r"(w), "r"(ep) : "memory");
}
template <int N, int S0, int S1, int W> __device__ __forceinline__ void gather_lazy(uint32_t (*v)[4], const uint4* p, uint32_t ep, int& budget, bool skip_last = false) {
#pragma unroll
  for (int i = 0; i < 4 * N; ++i) {
    if ((i & 3) == W) v[i >> 2][W] = N == 7 && i >= 24 && skip_last ? ep & 1u : ~ep;
    else if (N == 7 && i >= 24) v[6][i & 3] = 0;
    else asm volatile("" : "=r"(v[i >> 2][i & 3]));
  }
#pragma unroll 1
  do {
#pragma unroll
    for (int i = 0; i < N; ++i) ld_rlx4_stale(v[i], p + (i & 1) * S0 + (i >> 1) * S1, v[i][W], ep);
  } while (retry<1>(stale<N, W>(v, ep), budget));
}
template <int N, int STRIDE, int W> __device__ __forceinline__ void gather(uint32_t (*v)[4], const uint4* p, uint32_t ep, int& budget) {
#pragma unroll 1
  do {
#pragma unroll
    for (int i = 0; i < N; ++i) ld_rlx4(v[i], p + i * STRIDE);
  } while (retry<1>(stale<N, W>(v, ep), budget));
}
__device__ __forceinline__ void row_stats(float (&s)[4], float& qlo, float& qhi, const uint32_t (&x)[5][4], const uint32_t (&b)[10], int gq) {
  const float z[4] = {0.f, 0.f, 0.f, 0.f};
  float q[4][4];
#pragma unroll
  for (int i = 0; i < 5; ++i) {
    mma16(s, x[i], b[2 * i], b[2 * i + 1], i ? s : z);
#pragma unroll
    for (int e = 0; e < 4; ++e) mma8(q[e], x[i][e & 2], x[i][(e & 2) + 1], x[i][e], i ? q[e] : z);
  }
  const bool odd = gq & 1;
  qlo = (odd ? q[0][1] : q[0][0]) + (odd ? q[2][1] : q[2][0]);
  qhi = (odd ? q[1][3] : q[1][2]) + (odd ? q[3][3] : q[3][2]);
}
__device__ __forceinline__ uint32_t norm_word(float s, float q, float& mean, float& rstd) {
  mean = s * (1.f / 640.f);
  rstd = rsq(fmaxf(fmaf(q, 1.f / 640.f, -mean * mean), 0.f) + 1e-5f);
  return pack2(-mean * bf_round(rstd), rstd);
}
__device__ __forceinline__ uint32_t dup_lo(uint32_t w) { return __byte_perm(w, 0u, 0x1010); }
__device__ __forceinline__ uint32_t dup_hi(uint32_t w) { return __byte_perm(w, 0u, 0x3232); }

__device__ __forceinline__ void wgmma_n192(float (&d)[96], const uint32_t (&a)[4], uint64_t db, int add) {
  asm volatile("{.reg .pred p; setp.ne.b32 p, %101, 0; wgmma.mma_async.sync.aligned.m64n192k16.f32.bf16.bf16 "
    "{%0, %1, %2, %3, %4, %5, %6, %7, %8, %9, %10, %11, %12, %13, %14, %15, "
    "%16, %17, %18, %19, %20, %21, %22, %23, %24, %25, %26, %27, %28, %29, %30, %31, "
    "%32, %33, %34, %35, %36, %37, %38, %39, %40, %41, %42, %43, %44, %45, %46, %47, "
    "%48, %49, %50, %51, %52, %53, %54, %55, %56, %57, %58, %59, %60, %61, %62, %63, "
    "%64, %65, %66, %67, %68, %69, %70, %71, %72, %73, %74, %75, %76, %77, %78, %79, "
    "%80, %81, %82, %83, %84, %85, %86, %87, %88, %89, %90, %91, %92, %93, %94, %95}, "
    "{%96, %97, %98, %99}, %100, p, 1, 1, 1;}"
    : "+f"(d[0]), "+f"(d[1]), "+f"(d[2]), "+f"(d[3]), "+f"(d[4]), "+f"(d[5]), "+f"(d[6]), "+f"(d[7]),
      "+f"(d[8]), "+f"(d[9]), "+f"(d[10]), "+f"(d[11]), "+f"(d[12]), "+f"(d[13]), "+f"(d[14]), "+f"(d[15]),
      "+f"(d[16]), "+f"(d[17]), "+f"(d[18]), "+f"(d[19]), "+f"(d[20]), "+f"(d[21]), "+f"(d[22]), "+f"(d[23]),
      "+f"(d[24]), "+f"(d[25]), "+f"(d[26]), "+f"(d[27]), "+f"(d[28]), "+f"(d[29]), "+f"(d[30]), "+f"(d[31]),
      "+f"(d[32]), "+f"(d[33]), "+f"(d[34]), "+f"(d[35]), "+f"(d[36]), "+f"(d[37]), "+f"(d[38]), "+f"(d[39]),
      "+f"(d[40]), "+f"(d[41]), "+f"(d[42]), "+f"(d[43]), "+f"(d[44]), "+f"(d[45]), "+f"(d[46]), "+f"(d[47]),
      "+f"(d[48]), "+f"(d[49]), "+f"(d[50]), "+f"(d[51]), "+f"(d[52]), "+f"(d[53]), "+f"(d[54]), "+f"(d[55]),
      "+f"(d[56]), "+f"(d[57]), "+f"(d[58]), "+f"(d[59]), "+f"(d[60]), "+f"(d[61]), "+f"(d[62]), "+f"(d[63]),
      "+f"(d[64]), "+f"(d[65]), "+f"(d[66]), "+f"(d[67]), "+f"(d[68]), "+f"(d[69]), "+f"(d[70]), "+f"(d[71]),
      "+f"(d[72]), "+f"(d[73]), "+f"(d[74]), "+f"(d[75]), "+f"(d[76]), "+f"(d[77]), "+f"(d[78]), "+f"(d[79]),
      "+f"(d[80]), "+f"(d[81]), "+f"(d[82]), "+f"(d[83]), "+f"(d[84]), "+f"(d[85]), "+f"(d[86]), "+f"(d[87]),
      "+f"(d[88]), "+f"(d[89]), "+f"(d[90]), "+f"(d[91]), "+f"(d[92]), "+f"(d[93]), "+f"(d[94]), "+f"(d[95])
    : "r"(a[0]), "r"(a[1]), "r"(a[2]), "r"(a[3]), "l"(db), "r"(add));
}
__device__ __forceinline__ void wgmma_n48(float (&d)[24], const uint32_t (&a)[4], uint64_t db, int add) {
  asm volatile("{.reg .pred p; setp.ne.b32 p, %29, 0; wgmma.mma_async.sync.aligned.m64n48k16.f32.bf16.bf16 "
    "{%0, %1, %2, %3, %4, %5, %6, %7, %8, %9, %10, %11, %12, %13, %14, %15, "
    "%16, %17, %18, %19, %20, %21, %22, %23}, "
    "{%24, %25, %26, %27}, %28, p, 1, 1, 1;}"
    : "+f"(d[0]), "+f"(d[1]), "+f"(d[2]), "+f"(d[3]), "+f"(d[4]), "+f"(d[5]), "+f"(d[6]), "+f"(d[7]),
      "+f"(d[8]), "+f"(d[9]), "+f"(d[10]), "+f"(d[11]), "+f"(d[12]), "+f"(d[13]), "+f"(d[14]), "+f"(d[15]),
      "+f"(d[16]), "+f"(d[17]), "+f"(d[18]), "+f"(d[19]), "+f"(d[20]), "+f"(d[21]), "+f"(d[22]), "+f"(d[23])
    : "r"(a[0]), "r"(a[1]), "r"(a[2]), "r"(a[3]), "l"(db), "r"(add));
}
__device__ __forceinline__ void wgmma_n80(float (&d)[40], const uint32_t (&a)[4], uint64_t db, int add) {
  asm volatile("{.reg .pred p; setp.ne.b32 p, %45, 0; wgmma.mma_async.sync.aligned.m64n80k16.f32.bf16.bf16 "
    "{%0, %1, %2, %3, %4, %5, %6, %7, %8, %9, %10, %11, %12, %13, %14, %15, "
    "%16, %17, %18, %19, %20, %21, %22, %23, %24, %25, %26, %27, %28, %29, %30, %31, "
    "%32, %33, %34, %35, %36, %37, %38, %39}, "
    "{%40, %41, %42, %43}, %44, p, 1, 1, 1;}"
    : "+f"(d[0]), "+f"(d[1]), "+f"(d[2]), "+f"(d[3]), "+f"(d[4]), "+f"(d[5]), "+f"(d[6]), "+f"(d[7]),
      "+f"(d[8]), "+f"(d[9]), "+f"(d[10]), "+f"(d[11]), "+f"(d[12]), "+f"(d[13]), "+f"(d[14]), "+f"(d[15]),
      "+f"(d[16]), "+f"(d[17]), "+f"(d[18]), "+f"(d[19]), "+f"(d[20]), "+f"(d[21]), "+f"(d[22]), "+f"(d[23]),
      "+f"(d[24]), "+f"(d[25]), "+f"(d[26]), "+f"(d[27]), "+f"(d[28]), "+f"(d[29]), "+f"(d[30]), "+f"(d[31]),
      "+f"(d[32]), "+f"(d[33]), "+f"(d[34]), "+f"(d[35]), "+f"(d[36]), "+f"(d[37]), "+f"(d[38]), "+f"(d[39])
    : "r"(a[0]), "r"(a[1]), "r"(a[2]), "r"(a[3]), "l"(db), "r"(add));
}

__device__ __forceinline__ constexpr int wo_off(int i) { return (i < 4 ? 8 + i : i - 4) * WO; }
__device__ __forceinline__ void load_stage(const Params& P, uint32_t sb, int st, int j, int g, int rank) {
  const uint32_t fb = sb + OFF_BAR + 8 * (B_FULL + (st & 3)), a = sb + (st & 3) * STAGE;
  mbar_expect_tx(fb, STAGE);
  tma2(a, &P.xa, fb, 640 * rank + 64 * st, 128 * j);
  tma3_both(a + STAGE_A + rank * (STAGE_B0 / 2), &P.w0, fb, 80 * g, 64 * st + 32 * rank, 0);
  tma3_both(a + STAGE_A + STAGE_B0 + rank * (STAGE_B1 / 2), &P.w1, fb, 80 * g + 64, 64 * st + 32 * rank, 0);
}

__device__ __forceinline__ void run_producer(const Params& P, uint8_t* sm, uint32_t sb, int b, uint32_t t0) {
  const int rank = b & 1, g = (b >> 1) & 7, j = b >> 4;
  const uint32_t bar = sb + OFF_BAR;
#pragma unroll 1
  for (int st = 1; st < 10; ++st) {
    if (st == 2) {
      wait_until(t0 + WPF_AT);
      if (elect_one()) bulk_prefetch(P.wqkv + (128 + 4 * b) * 1920, 15360);
      bar_sync<NB_GO, 160>();
    }
    if (st == 9) bar_sync<NB_HELP, 128>();
    mbar_wait(bar + 8 * (B_EMPTY + (st & 3)), (((st + 1) >> 2) + 1) & 1);
    if (elect_one()) {
      load_stage(P, sb, st, j, g, rank);
      const int k = st - LMPF_AT;
      if ((uint32_t)k < 5u) bulk_prefetch(P.wmod + (5 * b + k) * 3840 + 1280, 5120);
      if (st == 7) bulk_prefetch(P.wo + b * 3200, 6400);
    }
  }
  TSTAMP(1);
#pragma unroll 1
  for (int i = 0; i < 8; ++i) {
    if (i < 2 || i == 4 || i == 7) mbar_wait(bar + 8 * (B_EMPTY + (i < 2 ? 2 + i : i & 1)), i == 0);
    if (elect_one()) {
      const uint32_t fb = bar + 8 * (i ? B_WO1 : B_WO0), a = sb + (i < 4 ? 8 + i : i - 4) * WO;
      if (i == 0) {
        mbar_expect_tx(bar + 8 * B_XS, 25600);
        tma2(sb + OFF_LM, &P.wm0, bar + 8 * B_XS, 1280 + 64 * (b & 31), 160 * (b >> 5));
        tma2(sb + OFF_LM + 20480, &P.wm1, bar + 8 * B_XS, 3328 + 16 * (b & 31), 160 * (b >> 5));
      }
      if (i < 2) mbar_expect_tx(fb, i ? 7 * 12800 : 12800);
      if ((i & 1) == rank) {
        const int k0 = 80 * (i ? i - (i <= g) : g);
        tma3_both(a, &P.woa, fb, 80 * g, k0, 0);
        tma2_both(a + 10240, &P.wob, fb, 80 * g + 64, k0);
      }
    }
  }
  TSTAMP(3);
  if (b < N_FFN) {
    if (elect_one()) {
      mbar_expect_tx(bar + 8 * B_ACT, 1024);
      mbar_expect_tx(bar + 8 * B_FFN, 40960);
    }
    uint32_t next = clock32();
#pragma unroll 1
    for (int i = 0; i < 6; ++i) {
      if (i == FFN_EARLY) {
        mbar_wait(bar + 8 * B_GO, 1);
        next = clock32();
      }
      if (i == 3) bar_sync<NB_LM, 128>();
      if (i == 4) next += DOWN_GAP;
      wait_until(next);
      next += FFN_GAP;
      if (elect_one())
        tma3(sb + OFF_FFN + 10240 * i, &P.wg + (i >> 1), bar + 8 * (i < 4 ? B_FFN : B_XS), i < 4 ? 32 * (b >> 1) : 0, i < 4 ? 0 : 16 * b, i < 4 ? 2 * rank + (i & 1) : 5 * (i & 1));
    }
  }
  TSTAMP(4);
}

__device__ __forceinline__ void run_helper(const Params& P, uint8_t* sm, uint32_t sb, int b, int hw, uint32_t ep, int budget, uint32_t poll_at) {
  const int h = threadIdx.x - 256, lane = h & 31, gq = lane >> 2, t = lane & 3, rank = b & 1, g = (b >> 1) & 7, j = b >> 4;
  const uint32_t bar = sb + OFF_BAR, prm = sb + OFF_PRM;
  uint4* const box = P.sc + b * BOX;
  const bool main20 = lane < 20;
  const int fin = 128 * (b >> 4) + 16 * ((b >> 2) & 3) + 2 * (b & 3) + (lane & 1) + 32 * (lane & 2) + 2 * (lane & 4);
  const int which = main20 ? 2 - hw : 3, fsl = (fin * 205) >> 14;
  const int q4 = main20 ? lane : min(10 * hw + lane - 20, 19);
  uint32_t wr[2];
  asm volatile("ld.global.nc.v2.u32 {%0, %1}, [%2];" : "=r"(wr[0]), "=r"(wr[1]) : "l"(P.wr + 80 * g + 4 * q4));
  uint32_t cw;
  asm volatile("ld.global.nc.u32 %0, [%1];" : "=r"(cw) : "l"(P.c + 160 * (b >> 5) + 2 * min(h, 79)));
  sts1(sb + OFF_SILU + 4 * min(h, 79), pack2(bf_lo(cw) * sigmoid(bf_lo(cw)), bf_hi(cw) * sigmoid(bf_hi(cw))));
  if (h < 4) sts1(prm + R_ONE + 4 * h, 0x3F803F80u);
  wait_until(poll_at);
  {
    uint32_t v[4][4];
    const int h80 = min(h, 79);
    const uint4* src = at<16>(P.sc + TABLES, 320 * j + h80);
#pragma unroll 1
    do {
#pragma unroll
      for (int i = 0; i < 4; ++i) ld_rlx4(v[i], src + i * 80);
    } while (retry<~0u>(stale<4, 2>(v, ep), budget));
#pragma unroll
    for (int i = 0; i < 4; ++i) sts2(sb + OFF_C1 + 16 * h80 + 1280 * (i & 1) + (i < 2 ? 8 : 0), v[i][0], v[i][1]);
    mbar_arrive(bar + 8 * B_TAB);
  }
  TSTAMP(3);
  bar_sync<NB_GO, 160>();
  {
    const char* src = hw == 2 ? at<128>(reinterpret_cast<const char*>(P.wdown), 160 * b + lane)
                              : at<128>(reinterpret_cast<const char*>(hw ? P.wup : P.wgate), (160 * (b & 3) + lane) * 27 + (b >> 2));
    uint4* slot = at<16>(box + M_HALO, h);
    uint32_t next = clock32() + TOUCH_AT + hw * (TOUCH_GAP / 3);
#pragma unroll 1
    for (int i = 0; i < 5; ++i) {
      wait_until(next);
      next += TOUCH_GAP;
      if (b < N_FFN) asm volatile("cp.async.cg.shared.global.L2::128B [%0], [%1], 16;" ::"r"(sb + OFF_SINK + 16 * h), "l"(src) : "memory");
      src += hw == 2 ? 4096 : 32 * 3456;
      if (i < 4) {
        st_rlx4(slot, ~ep, ~ep, ~ep, ~ep);
        st_rlx4(slot + 96, ~ep, ~ep, ~ep, ~ep);
      }
      slot += 192;
    }
  }
  bar_sync<NB_HELP, 128>();
  TSTAMP(5);

  {
    float d0[4] = {0.f, 0.f, 0.f, 0.f}, d1[4] = {0.f, 0.f, 0.f, 0.f};
    const uint32_t row = 8 * (lane >> 4) + (lane & 7), half = (lane >> 3) & 1, kstep = hw < 2 ? 2048 : 512;
    uint32_t wa = sb + OFF_LM + (hw < 2 ? row * 128 + (((4 * hw + half) ^ (lane & 7)) << 4) : 20480 + row * 32 + ((half ^ ((lane >> 2) & 1)) << 4)), sa = sb + OFF_SILU + (lane >> 3) * 16;
    mbar_wait(bar + 8 * B_XS, 1);
    {
      uint32_t hv[2][4] = {};
      const int q = min(2 * hw, 3);
      const uint4* const src = at<16>(box + (M_HALO - 16 * BOX), 32 * q + lane);
      mbar_wait(bar + 8 * B_EMPTY, 0);
      wait_until(clock32() + HALO_GAP);
      if (j > 0) gather<2, 32, 0>(hv, src, ep, budget);
      stsm4(sb + OFF_H + 512 * q + 16 * lane, hv[0]);
      stsm4(sb + OFF_H + 512 * q + 16 * lane + 512, hv[1]);
      bar_arrive<NB_HALO, 128>();
      if (j > 0) TSTAMP(4);
    }
    mbar_wait(bar + 8 * (B_EMPTY + 1), 0);
    TSTAMP(6);
    const uint32_t o1 = hw < 2 ? (wa ^ 32) - wa : 1024, s1 = hw < 2 ? 0 : 64;
#pragma unroll 1
    for (int u = hw < 2 ? 0 : 2; u < 5; ++u) {
      uint32_t a[4][4], s[2][4];
      ldsm4(s[0], sa);
      ldsm4t(a[0], wa);
      ldsm4t(a[1], wa + o1);
      ldsm4(s[1], sa + s1);
      ldsm4t(a[2], wa + kstep);
      ldsm4t(a[3], wa + kstep + o1);
      sched_fence(P.zero);
      mma16(d0, a[0], s[0][0], s[0][1], d0);
      if (hw < 2 || u < 4) mma16(d1, a[1], s[1][0], s[1][1], d1);
      mma16(d0, a[2], s[0][2], s[0][3], d0);
      if (hw < 2 || u < 4) mma16(d1, a[3], s[1][2], s[1][3], d1);
      wa += hw < 2 ? 4096 : 2048;
      sa += 64 + s1;
    }
    if (hw == 2) {
      d0[0] += d1[0];
      d0[2] += d1[2];
    }
    const float v = t & 2 ? (t & 1 ? d1[2] : d1[0]) : (t & 1 ? d0[2] : d0[0]);
    if (32 * hw + 8 * t < 80) st_rlx1(at<4>(box + M_LATE, 32 * hw + 8 * t + gq), tag(u32(v), ep));
  }
  if (b < N_FFN) {
    if (h == 0) mbar_expect_tx(bar + 8 * B_XS, 20480);
    bar_arrive<NB_LM, 128>();
  }
  TSTAMP(7);
  wait_until(clock32() + LATE_GAP);
  {
    uint32_t v[4][4];
    const int q = 160 * which + (main20 || hw < 2 ? 20 * g + q4 : min(fin >> 2, 159));
    const uint4* src = at<16>(P.sc + M_LATE, q < 512 ? (q >> 4) * BOX + (q & 15) : ((q - 512) >> 2) * BOX + 16 + (q & 3));
#pragma unroll 1
    do {
#pragma unroll
      for (int i = 0; i < 4; ++i) ld_rlx4(v[i], src + i * 32 * BOX);
    } while (retry<1>(stale<4, 0>(v, ep) | stale<4, 1>(v, ep) | stale<4, 2>(v, ep) | stale<4, 3>(v, ep), budget));
    const uint32_t one = which == 2 ? 0x3F803F80u : 0u;
    uint32_t w[2], pw[2];
#pragma unroll
    for (int e = 0; e < 2; ++e) {
      w[e] = fma2(pack2(f32(v[0][2 * e]) + f32(v[1][2 * e]) + f32(v[2][2 * e]) + f32(v[3][2 * e]),
                        f32(v[0][2 * e + 1]) + f32(v[1][2 * e + 1]) + f32(v[2][2 * e + 1]) + f32(v[3][2 * e + 1])), 0x3F803F80u, one);
      pw[e] = fma2(w[e], wr[e], 0x80008000u);
    }
    const uint32_t dst = prm + (main20 || hw < 2 ? 160 * which + 8 * q4 : R_FIN + 4 * (lane & 6));
    sts2(dst, w[0], w[1]);
    sts2(dst + 800, pw[0], pw[1]);
    float s = main20 ? bf_lo(pw[0]) + bf_hi(pw[0]) + bf_lo(pw[1]) + bf_hi(pw[1]) : 0.f;
#pragma unroll
    for (int o = 16; o > 0; o >>= 1) s += shx(s, o);
    sts1(sb + OFF_KEY + 64 + 4 * hw, u32(s));
    mbar_arrive(bar + 8 * B_TAB);
    mbar_wait(bar + 8 * B_TAB, 1);
  }
  TSTAMP(8);

  uint32_t ckey = 0;
  uint4* const odst = reinterpret_cast<uint4*>(P.out + (256 * j + rank) * 640 + 80 * g);
  if (hw == 0) {
    const uint32_t tile = min(4 * (lane & 3) + (lane >> 3), 9) * 16;
    uint32_t c1[4], sv[4], gb[4], x[4];
    ldsm4(c1, prm + R_C1 + tile);
    ldsm4(sv, prm + R_SB + tile);
    ldsm4(gb, prm + (lane & 4 ? R_GB + tile : R_ONE));
    const uint32_t bc = lds1(sb + OFF_KEY + 68), keep = lop3<0xF0>(gq & 4 ? ~0u : 0u, 0u, 0u);
    uint4* const cdst = at<16>(P.sc + M_CAND, (b - rank + (lane >> 4)) * BOX + 2 * (lane & 12) + 4 * rank + (lane & 3));
    uint32_t crow;
    {
      sched_fence(P.zero);
      bar_sync<NB_KEY, 288>();
      uint32_t k4[4];
      lds4(k4, sb + OFF_ROWS + 16 * lane);
      ckey = __reduce_max_sync(0xFFFFFFFFu, max(max(k4[0], k4[1]), max(k4[2], k4[3])));
      crow = (~ckey >> 1) & 127;
      TSTAMP(9);
      const uint32_t nw = lds1(sb + OFF_ROWS + 512 + 4 * crow);
      ldsm4(x, sb + OFF_X2 + crow * 176 + tile);
      const uint32_t rs = dup_hi(nw), nm = dup_lo(nw);
#pragma unroll
      for (int e = 0; e < 4; ++e) x[e] = fma2(gb[e], fma2(fma2(x[e], rs, nm), c1[e], sv[e]), x[e] & keep);
      st_rlx4(cdst, tag(x[0], ep), x[1], gq == 2 ? ckey : x[2], gq == 2 ? bc : x[3]);
    }
    bar_arrive<NB_PUB, 288>();
    TSTAMP(10);
    bar_sync<NB_OUT + 1, 160>();
    uint32_t next = clock32() + OUT_AT;
#pragma unroll 1
    for (int u = 0; u < 8; ++u) {
      if (u == 4) {
        bar_sync<NB_OUT, 160>();
        next = clock32();
      }
      wait_until(next);
      next += OUT_GAP;
      if (u != crow >> 4 && elect_one())
        asm volatile("cp.async.bulk.tensor.2d.global.shared::cta.bulk_group [%0, {%2, %3}], [%1];"
                     ::"l"(&P.om), "r"(sb + OFF_OUT + 2560 * u), "r"(640 * rank + 80 * g), "r"(128 * j + 16 * u) : "memory");
    }
    asm volatile("cp.async.bulk.commit_group;" ::: "memory");
    TSTAMP(11);
  } else {
    if (b >= 80 || hw == 2) return;
    bar_sync<NB_WIN, 64>();
  }
  uint32_t m[7][4], wkey = lds1(sb + OFF_KEY + 80);
  if (b >= N_FFN) {
    gather<1, 0, 0>(m, at<64>(P.sc + M_CAND + 16, (lane & 14) * (2 * BOX) + (lane & 1)), ep, budget);
    wkey = __reduce_max_sync(0xFFFFFFFFu, m[0][2]);
  }
  const uint32_t wtok = ~wkey & 2047;
  TSTAMP(12);
  if (hw == 0) {
    const uint32_t u = (~ckey >> 5) & 7, skip = ckey == wkey ? (~ckey >> 1) & 15 : 16;
#pragma unroll
    for (int i = 0; i < 5; ++i) {
      const uint32_t v = lane + 32 * i, r = (v * 205) >> 11;
      if (r != skip) *at<16>(odst, 2560 * u + v + 150 * r) = *reinterpret_cast<const uint4*>(sm + OFF_OUT + 2560 * u + 16 * v);
    }
    st_rlx1(at<4>(box + M_EPOCH, lane), ep);
    asm volatile("cp.async.bulk.wait_group.read 0;" ::: "memory");
    TSTAMP(15);
    TALIGN(1);
    return;
  } else {
    const int cn = fin - 80 * fsl;
    gather<1, 0, 0>(m, at<16>(P.sc + M_CAND, (16 * (wtok >> 8) + (lane & 8 ? 2 * (lane & 7) : 2 * fsl + 1)) * BOX + 4 * (wtok & 1) +
                                             (lane & 8 ? 16 : 8 * (cn >> 5) + ((cn >> 1) & 3))), ep, budget);
    const uint32_t bw = cn & 16 ? (cn & 8 ? m[0][3] : m[0][2]) : (cn & 8 ? m[0][1] : m[0][0]);
    const uint32_t gw = lds1(prm + R_FIN + 4 * (lane & 6) + 4 * (b & 1));
    float r = f32(m[0][3]);
#pragma unroll
    for (int o = 1; o < 8; o <<= 1) r += shx(r, o);
    r = __shfl_sync(0xFFFFFFFFu, r, 8) + f32(wkey >> 31 ? wkey & 0x7FFFF800u : ~wkey | 0x7FFu);
    const float sg = bf_round(sigmoid(bf_round(r))), gv = lane & 1 ? bf_hi(gw) : bf_lo(gw), bv = lane & 1 ? bf_hi(bw) : bf_lo(bw);
    __nv_bfloat16* const dst = at<2>(P.out, wtok * 640 + fin);
    const uint4* const src = at<16>(P.sc + M_YP, (4 * (lane >> 3) + ((b >> 2) & 3)) * BOX + 32 * j + 8 * (b & 3) + (lane & 7));
    TSTAMP(13);
    bar_sync<NB_YP, 64>();
    wait_until(clock32() + YP_GAP);
    gather_lazy<7, 16 * BOX, 32 * BOX, 0>(m, src, ep, budget, lane >= 24);
    TSTAMP(14);
    float y[4];
#pragma unroll
    for (int e = 0; e < 4; ++e)
      y[e] = ((f32(m[0][e]) + f32(m[1][e])) + (f32(m[2][e]) + f32(m[3][e]))) + ((f32(m[4][e]) + f32(m[5][e])) + f32(m[6][e]));
    const bool u1 = lane & 2, u2 = lane & 4;
    const float e0 = (u1 ? y[1] : y[0]) + shx(u1 ? y[0] : y[1], 2), e1 = (u1 ? y[3] : y[2]) + shx(u1 ? y[2] : y[3], 2);
    float e = (u2 ? e1 : e0) + shx(u2 ? e0 : e1, 4);
    e += shx(e, 8);
    e += shx(e, 16);
    asm volatile("{.reg .pred p; setp.lt.u32 p, %2, 8; @p st.global.b16 [%0], %1;}"
                 ::"l"(dst), "h"((uint16_t)pack2(fmaf(gv, bf_round(bf_round(e) * sg), bv), 0.f)), "r"(lane) : "memory");
  }
  TSTAMP(15);
}

#define ACC(part, i, e) ((i) < 8 ? accA[32 * (part) + 4 * ((i) & 7) + (e)] : accB[8 * (part) + 4 * ((i) & 1) + (e)])
__device__ __forceinline__ constexpr int kpos(int i) { return i == 2 ? 8 : i == 7 ? 9 : i - (i > 2) - (i > 7); }

__device__ __forceinline__ void run_consumer(const Params& P, uint8_t* sm, uint32_t sb, int b, int warp, uint32_t ep, int budget) {
  const int tid = keep(threadIdx.x ^ 2), lane = tid & 31, gq = lane >> 2, t = lane & 3, p = warp >> 2, wq = warp & 3, rb = warp ^ 4;
  const int rank = b & 1, g = (b >> 1) & 7, j = b >> 4;
  const uint32_t bar = sb + OFF_BAR;
  uint4* const box = P.sc + b * BOX;
  const float z4[4] = {0.f, 0.f, 0.f, 0.f};

  uint32_t nrm[4];
  {
    uint32_t x[5][4], ones[10];
#pragma unroll
    for (int i = 0; i < 10; ++i) ones[i] = 0x3F803F80u;
    uint4* const dst = at<8>(box + M_ST1, tid >> 4);
    mbar_wait(bar + 8 * B_XS, 0);
    asm volatile("cp.async.wait_all;" ::: "memory");
    TSTAMP(4);
#pragma unroll
    for (int i = 0; i < 5; ++i) lds4(x[i], sb + OFF_XS + 4096 * i + 16 * tid);
    float s[4], qlo, qhi, mean, rstd;
    row_stats(s, qlo, qhi, x, ones, gq);
    const float q = __shfl_sync(0xFFFFFFFFu, qlo + qhi, 4 * gq + (gq >> 1));
    float v = t & 1 ? q : s[0] + s[2];
    v += shx(v, 4);
    v += shx(v, 8);
    const uint32_t nw = norm_word(v, shx(v, 1), mean, rstd);
    if ((lane & 15) == 0) st_rlx2(dst, nw, ep);
    TSTAMP(5);
    asm volatile("setmaxnreg.inc.sync.aligned.u32 224;");
  }

  float accA[96], accB[24];
#pragma unroll
  for (int i = 0; i < 96; ++i) asm volatile("" : "=f"(accA[i]));
#pragma unroll
  for (int i = 0; i < 24; ++i) asm volatile("" : "=f"(accB[i]));
  uint32_t xr[5][4];
#pragma unroll
  for (int i = 0; i < 20; ++i) asm volatile("" : "=r"(xr[i >> 2][i & 3]));
  const uint32_t turn = keep(NB_TURN + (tid >> 7)), pass = keep(NB_TURN + 1 - (tid >> 7));
  uint4* const opub = reinterpret_cast<uint4*>(__shfl_xor_sync(0xFFFFFFFFu, reinterpret_cast<uintptr_t>(at<16>(box + M_O, tid ^ 2)), 2));
  const uint4* src[7];
  const uint4* const lower = reinterpret_cast<const uint4*>(__shfl_xor_sync(0xFFFFFFFFu, reinterpret_cast<uintptr_t>(at<16>(P.sc + M_O, (b & ~14) * BOX + (tid ^ 2))), 2));
  const int l2 = lane ^ 2;
  const uint32_t ha = keep(sb + OFF_H + rb * 2560 + 16 * l2), lo = keep(sb + OFF_L + rb * 1280 + 16 * l2);
  const uint32_t va = keep(sb + OFF_H + 1280 + (rb + ((lane >> 3) & 1)) * 2560 + (lane >> 4) * 128 + (l2 & 7) * 16);
  const uint32_t M = keep((2 * (t ^ 2) > gq ? 0xFFFFu : 0u) | (2 * (t ^ 2) + 1 > gq ? 0xFFFF0000u : 0u)), gk = keep(g + (tid >> 9));
  {
    uint32_t la = keep(sb + (16 * rb + (l2 & 15)) * 128 + (((lane >> 4) ^ (l2 & 7)) << 4)), c1a = sb + OFF_C1 + 16 * t;
    const uint32_t rel = keep(map_to_cta(bar + 8 * B_EMPTY + 16, lane & 1)), y0 = keep(8 * ((5 * g >> 2) + 1) + (tid >> 9));
    const bool two = (ha & 0x1E0) == 0;
    const uint64_t dbase = make_desc(sb + STAGE_A, 4096, 1024, 1);
    uint64_t d0 = dbase;
    uint32_t raw[4][4], cw[4][4], y = 8;
    int add = 0;
    if (p == 1) turn_pass(pass);
    {
      const uint4* const src = at<8>(P.sc + M_ST1, (16 * j + 2 * rb) * 2 * BOX + 2 * gq + rank);
      mbar_wait(bar + 8 * B_FULL, 0);
#pragma unroll
      for (int k = 0; k < 4; ++k) ldsm4(raw[k], la ^ (32 * k));
      uint32_t n0[2], n1[2];
#pragma unroll 1
      do {
        ld_rlx2(n0, src);
        ld_rlx2(n1, src + BOX);
      } while (retry<~0u>(neq2(n0[1], n1[1], ep), budget));
      TSTAMP(6);
      mbar_wait(bar + 8 * B_TAB, 0);
      if (warp == 0) bar_arrive<NB_GO, 160>();
#pragma unroll
      for (int k = 0; k < 4; ++k) lds4(cw[k], c1a + 64 * k);
      nrm[0] = dup_hi(n0[0]); nrm[1] = dup_hi(n1[0]); nrm[2] = dup_lo(n0[0]); nrm[3] = dup_lo(n1[0]);
    }
    TSTAMP(7);
#pragma unroll 1
    for (;;) {
      uint32_t af[4][4];
      c1a += 256;
#pragma unroll
      for (int k = 0; k < 16; ++k) raw[k >> 2][k & 3] = fma2(raw[k >> 2][k & 3], nrm[k & 1], nrm[2 + (k & 1)]);
      wg_wait();
      if (two) mbar_arrive_cluster(rel ^ (y & 24));
#pragma unroll
      for (int k = 0; k < 16; ++k) af[k >> 2][k & 3] = fma2(raw[k >> 2][k & 3], cw[k >> 2][(k >> 1) & 1], cw[k >> 2][2 + ((k >> 1) & 1)]);
#pragma unroll
      for (int k = 0; k < 4; ++k) lds4(cw[k], c1a + 64 * k);
      wg_fence();
      turn_wait(turn);
      constexpr uint64_t D1 = (STAGE_B0 >> 4) + ((uint64_t)64 << 16) - ((uint64_t)256 << 16) + ((uint64_t)16 << 32) - ((uint64_t)64 << 32) + ((uint64_t)2 << 62);
#pragma unroll
      for (int k = 0; k < 4; ++k) {
        wgmma_n192(accA, af[k], d0 + ((k >> 1) * (STAGE_B0 / 2) + (k & 1) * 2048 >> 4), k ? 1 : add);
        if (PASS1 == 2 * k) turn_pass(pass);
        wgmma_n48(accB, af[k], d0 + (D1 + ((k >> 1) * (STAGE_B1 / 2) + (k & 1) * 512 >> 4)), k ? 1 : add);
        if (PASS1 == 2 * k + 1) turn_pass(pass);
      }
      wg_commit();
      if (__any_sync(0xFFFFFFFFu, y - y0 < 16u)) {
#pragma unroll
        for (int i = 0; i < 5; ++i) {
          const uint32_t k = 160 * g + 32 * i + 128 - 16 * y;
          if (k < 128u) ldsm4(xr[i], la ^ k);
        }
      }
      if (y == 80) break;
      const bool wrap = (uint32_t)d0 == (uint32_t)dbase + (3 * STAGE >> 4);
      la += wrap ? -3 * STAGE : STAGE;
      d0 = wrap ? dbase : d0 + (STAGE >> 4);
      add = 1;
      mbar_wait(bar + (y & 24), (y >> 5) & 1);
#pragma unroll
      for (int k = 0; k < 4; ++k) ldsm4(raw[k], la ^ (32 * k));
      y += 8;
    }
    wg_wait();
    if (two) mbar_arrive_cluster(rel - 8);
  }
  TSTAMP(8);

  uint32_t o[5][4];
  {
    uint32_t hi[20], vl[10], kl[10], kh[10], vv[20], qf[4][4], qs[4][2];
#pragma unroll
    for (int i = 0; i < 10; ++i) {
      hi[kpos(i)] = pack2(ACC(1, i, 2), ACC(1, i, 3));
      hi[10 + i] = pack2(ACC(2, i, 2), ACC(2, i, 3));
    }
#pragma unroll
    for (int q = 0; q < 5; ++q) hi[4 * q] = tag(hi[4 * q], ep);
    if (rb == 7) {
#pragma unroll
      for (int q = 0; q < 5; ++q) st_rlx4(opub + (M_HALO - M_O - 96 + 32 * q), hi + 4 * q);
    }
    if (HALO_FENCE) sched_fence(P.zero);
    TSTAMP(29);
#pragma unroll
    for (int i = 0; i < 10; ++i) kl[kpos(i)] = pack2(ACC(1, i, 0), ACC(1, i, 1));
#pragma unroll
    for (int hd = 0; hd < 4; ++hd) {
      const int f0 = 5 * (hd >> 1) + 3 * (hd & 1), sg = 5 * (hd >> 1) + 2;
      const bool mine = (t >> 1) == (hd & 1);
#pragma unroll
      for (int e = 0; e < 4; ++e) qf[hd][e] = pack2(ACC(0, f0 + (e >> 1), 2 * (e & 1)), ACC(0, f0 + (e >> 1), 2 * (e & 1) + 1));
#pragma unroll
      for (int e = 0; e < 2; ++e) {
        if (!(hd & 1)) qs[hd + 1][e] = pack2(ACC(0, sg, 2 * e), ACC(0, sg, 2 * e + 1));
        qs[hd][e] = mine ? qs[hd | 1][e] : 0u;
      }
    }
    sched_fence(P.zero);
#pragma unroll
    for (int q = 0; q < 5; ++q) stsm4(ha + 2560 + 512 * q, hi + 4 * q);
#pragma unroll
    for (int i = 0; i < 10; ++i) vl[i] = pack2(ACC(2, i, 0), ACC(2, i, 1));
    stsm4(lo, vl);
    stsm4(lo + 512, vl + 4);
    stsm2(lo + 1024, vl + 8);
    __syncwarp();
    if (lane == 0) mbar_arrive(bar + 8 * B_HALO);
    float S0[4][4], S1[4][4], S2[4][4];
    ldsm4t(vl, lo);
    ldsm4t(vl + 4, lo + 512);
    ldsm2t(vl + 8, lo + 1024);
#pragma unroll
    for (int hd = 0; hd < 4; ++hd) {
      mma16(S1[hd], qf[hd], kl[2 * hd], kl[2 * hd + 1], z4);
      mma16(S2[hd], qf[hd], hi[2 * hd], hi[2 * hd + 1], z4);
    }
#pragma unroll
    for (int hd = 0; hd < 4; ++hd) {
      mma8(S1[hd], qs[hd][0], qs[hd][1], kl[8 + (hd >> 1)], S1[hd]);
      mma8(S2[hd], qs[hd][0], qs[hd][1], hi[8 + (hd >> 1)], S2[hd]);
    }
    const bool up0 = M == ~0u, up1 = M != 0;
    uint32_t pp[4][2];
    const auto softmax = [&](const float (&A)[4][4], const float (&B)[4][4], int e) {
      const float SC = 0.22360679774997896f * 1.4426950408889634f;
      float a[4][2], mx[4];
#pragma unroll
      for (int hd = 0; hd < 4; ++hd) {
        a[hd][0] = up0 ? A[hd][2 * e] : B[hd][2 * e];
        a[hd][1] = up1 ? A[hd][2 * e + 1] : B[hd][2 * e + 1];
        mx[hd] = fmaxf(a[hd][0], a[hd][1]);
      }
#pragma unroll
      for (int s = 1; s < 4; s <<= 1) {
#pragma unroll
        for (int hd = 0; hd < 4; ++hd) mx[hd] = fmaxf(mx[hd], shx(mx[hd], s));
      }
#pragma unroll
      for (int hd = 0; hd < 4; ++hd) {
        const float ms = mx[hd] * -SC;
        pp[hd][e] = pack2(ex2(fmaf(a[hd][0], SC, ms)), ex2(fmaf(a[hd][1], SC, ms)));
      }
    };
    if (HI_FIRST) softmax(S1, S2, 1);
#pragma unroll
    for (int i = 0; i < 7; ++i)
      asm volatile("{.reg .pred p; setp.gt.u32 p, %1, %2; selp.b64 %0, %3, %4, p;}" : "=l"(src[i]) : "r"(gk), "r"(i), "l"(lower), "l"(lower + 2 * BOX));
    if (HI_FIRST) sched_fence(P.zero);
    TSTAMP(9);
    mbar_wait(bar + 8 * B_HALO, 0);
    if (rb == 0) bar_sync<NB_HALO, 128>();
    TSTAMP(10);
    ldsm4(kh, ha);
    ldsm4(kh + 4, ha + 512);
    ldsm2(kh + 8, ha + 1024);
#pragma unroll
    for (int i = 0; i < 5; ++i) ldsm4t(vv + 4 * i, va + 256 * i);
    const float ev = (j | rb) == 0 ? -1e9f / 0.22360679774997896f : 0.f, e4[4] = {ev, ev, ev, ev};
#pragma unroll
    for (int hd = 0; hd < 4; ++hd) mma16(S0[hd], qf[hd], kh[2 * hd], kh[2 * hd + 1], e4);
#pragma unroll
    for (int hd = 0; hd < 4; ++hd) mma8(S0[hd], qs[hd][0], qs[hd][1], kh[8 + (hd >> 1)], S0[hd]);
    if (!HI_FIRST) softmax(S1, S2, 1);
    softmax(S0, S1, 0);
    float L[4][4], O[4][3][4];
#pragma unroll
    for (int hd = 0; hd < 4; ++hd) mma8(L[hd], pp[hd][0], pp[hd][1], 0x3F803F80u, z4);
#pragma unroll
    for (int hd = 0; hd < 4; ++hd) {
      const uint32_t p0 = pp[hd][0] & M, p2 = pp[hd][0] & ~M, p3 = pp[hd][1] & M, p5 = pp[hd][1] & ~M;
      const uint32_t z0 = pp[hd][0] & P.zero, z1 = pp[hd][1] & P.zero;
#pragma unroll
      for (int e = 0; e < 3; ++e) {
        const int f = 5 * (hd >> 1) + 2 * (hd & 1) + e;
        mma16(O[hd][e], p0, z0, z1, p5, vv[2 * f], vv[2 * f + 1], z4);
      }
#pragma unroll
      for (int e = 0; e < 3; ++e) mma8(O[hd][e], p2, p3, vl[5 * (hd >> 1) + 2 * (hd & 1) + e], O[hd][e]);
    }
    const bool odd = t >> 1;
#pragma unroll
    for (int hp = 0; hp < 2; ++hp) {
      const float (&A)[3][4] = O[2 * hp];
      const float (&B)[3][4] = O[2 * hp + 1];
#pragma unroll
      for (int e = 0; e < 2; ++e) {
        const float ra = rcp(L[2 * hp][2 * e]), rc = rcp(L[2 * hp + 1][2 * e]), rm = odd ? rc : ra;
        uint32_t* const d = &o[0][0] + 10 * hp + e;
        d[0] = pack2(A[0][2 * e] * ra, A[0][2 * e + 1] * ra);
        d[2] = pack2(A[1][2 * e] * ra, A[1][2 * e + 1] * ra);
        d[4] = pack2((odd ? B[0][2 * e] : A[2][2 * e]) * rm, (odd ? B[0][2 * e + 1] : A[2][2 * e + 1]) * rm);
        d[6] = pack2(B[1][2 * e] * rc, B[1][2 * e + 1] * rc);
        d[8] = pack2(B[2][2 * e] * rc, B[2][2 * e + 1] * rc);
      }
      if (hp == 0) {
#pragma unroll
        for (int s = 0; s < 2; ++s) {
          o[s][0] = tag(o[s][0], ep);
          st_rlx4(opub + 256 * s, o[s]);
        }
        sched_fence(P.zero);
        if (p == 1) bar_arrive<NB_PV, 256>();
      }
    }
#pragma unroll
    for (int s = 2; s < 5; ++s) o[s][0] = tag(o[s][0], ep);
  }
  TSTAMP(11);

  float acc[40];
#pragma unroll
  for (int i = 0; i < 40; ++i) asm volatile("" : "=f"(acc[i]));
  uint32_t ga[10], pb[10], uw;
  uint4* const sdst = at<16>(box + M_ST2, 16 * rb + gq);
  const uint32_t prow = sb + OFF_PRM + (lane >> 3) * 16;
  {
    const uint64_t dw = make_desc(sb, 5120, 512, 2);
    uint32_t in[5][7][4];
    const auto fetch = [&](int s) {
#pragma unroll
      for (int i = 0; i < 7; ++i) ld_rlx4(in[s][i], src[i] + (2 * BOX * i + 256 * s));
    };
    st_rlx4(opub + 256 * 2, o[2]);
    mbar_wait(bar + 8 * B_WO0, 0);
    if (p == 0) bar_sync<NB_PV, 256>();
    fetch(0);
    wg_fence();
    turn_wait(turn);
#pragma unroll
    for (int s = 0; s < 5; ++s) {
      wgmma_n80(acc, o[s], dw + (wo_off(0) + 1024 * s >> 4), s);
      if (s == PASS0) turn_pass(pass);
    }
    wg_commit();
    TSTAMP(12);
    mbar_wait(bar + 8 * B_WO1, 0);
    sched_fence(P.zero);
#pragma unroll 1
    while (retry<1>(stale<7, 0>(in[0], ep), budget)) {
#pragma unroll
      for (int i = 0; i < 7; ++i) ld_rlx4_stale(in[0][i], src[i] + 2 * BOX * i, in[0][i][0], ep);
    }
    TSTAMP(13);
    fetch(1);
    st_rlx4(opub + 256 * 3, o[3]);
    st_rlx4(opub + 256 * 4, o[4]);
#pragma unroll
    for (int s = 0; s < 5; ++s) {
      if (s == FGO_STEP && tid == 128) mbar_arrive(bar + 8 * B_GO);
      wg_fence();
      turn_wait(turn);
#pragma unroll
      for (int i = 0; i < 7; ++i) {
        wgmma_n80(acc, in[s][i], dw + (wo_off(i + 1) + 1024 * s >> 4), 1);
        if (i == PASS_AT - 1) {
          if (s < 4 || p == 0) turn_pass(pass);
          if (s == 4) {
            wg_commit();
            wg_fence();
          }
          if (s + AHEAD > 1 && s + AHEAD < 5) {
            wg_commit();
            asm volatile("wgmma.wait_group.sync.aligned %0;" ::"n"(AHEAD == 1 ? 3 : 1) : "memory");
            fetch(s + AHEAD);
            wg_fence();
          }
        }
      }
      wg_commit();
    }
    sched_fence(P.zero);
    asm volatile("wgmma.wait_group.sync.aligned 2;" ::: "memory");
    mbar_wait(bar + 8 * B_TAB, 1);
    ld_row(ga, prow + R_GA);
    ldsm4(pb, lane & 1 ? prow + R_P : sb + OFF_PRM + R_ONE);
    ldsm4(pb + 4, lane & 1 ? prow + R_P + 64 : sb + OFF_PRM + R_ONE);
    ldsm2(pb + 8, lane & 1 ? prow + R_P + 128 : sb + OFF_PRM + R_ONE);
    uw = tag(lds1(sb + OFF_KEY + 64), ep);
    const uint32_t bad = stale<28, 0>(in[1], ep) | FORCE_REDO;
    uint32_t redo;
    asm volatile("{.reg .pred p; setp.ne.u32 p, %1, 0; barrier.cta.red.or.aligned.pred p, %2, 128, p; selp.u32 %0, 1, 0, p;}"
                 : "=r"(redo) : "r"(bad & 1u), "r"(turn + (NB_REDO - NB_TURN)) : "memory");
    if (redo) {
      TSTAMP(17);
#pragma unroll 1
      for (int q = 0; q < 40; ++q) {
        const int i = q & 7, s = q >> 3;
        uint32_t a[1][4];
        wg_wait();
        gather<1, 0, 0>(a, lower + (2 * BOX * (i ? i - (i <= g) : g) + 256 * s), ep, budget);
        wg_fence();
        wgmma_n80(acc, a[0], dw + ((i < 4 ? 8 + i : i - 4) * WO + 1024 * s >> 4), q);
        wg_commit();
      }
    }
    wg_wait();
  }
  TSTAMP(18);

  uint32_t c1[10], sv[10], gb[10], nw;
  const uint32_t trow = 16 * rb + (lane & 15), xt = sb + (lane >> 4) * 16;
  {
#pragma unroll
    for (int k = 0; k < 20; ++k) acc2(xr[k >> 2][k & 3], ga[k >> 1], pack2(acc[2 * k], acc[2 * k + 1]));
    float s[4], qlo, qhi;
    row_stats(s, qlo, qhi, xr, pb, gq);
    if (t == gq >> 1) {
      st_rlx4(sdst, u32(s[0]), u32(s[1]), u32(qlo), uw);
      st_rlx4(sdst + 8, u32(s[2]), u32(s[3]), u32(qhi), uw);
    }
    sched_fence(P.zero);
    TSTAMP(19);
    const uint32_t tok = keep(256 * j + 32 * rb + (l2 & 30) + rank), kdst = keep(sb + OFF_ROWS + 64 * rb + 2 * (l2 & 30) + 512 * (lane & 1));
#pragma unroll
    for (int s5 = 0; s5 < 5; ++s5) stsm4(xt + trow * 176 + (OFF_X2 + 32 * s5), xr[s5]);
    uint32_t m[4][4];
    ld_row(c1, prow + R_C1);
    ld_row(sv, prow + R_SB);
    ld_row(gb, prow + R_GB);
    if (ST2_GAP) wait_until(clock32() + ST2_GAP);
    gather_lazy<4, 2 * BOX, 4 * BOX, 3>(m, at<16>(P.sc + M_ST2, (16 * j + rank + 8 * (lane & 1)) * BOX + 16 * rb + (lane >> 1)), ep, budget);
    TSTAMP(20);
#pragma unroll
    for (int e = 0; e < 4; ++e) {
      s[e] = (f32(m[0][e]) + f32(m[1][e])) + (f32(m[2][e]) + f32(m[3][e]));
      s[e] += shx(s[e], 1);
    }
    float mean, rstd;
    nw = norm_word(s[0], s[2], mean, rstd);
    const uint32_t u = u32(rstd * fmaf(-mean, s[3], s[1]));
    const uint32_t key = ((u ^ ((uint32_t)((int)u >> 31) | 0x80000000u)) | 2047u) ^ tok;
    sts1(kdst, lane & 1 ? nw : key);
    bar_arrive<NB_KEY, 288>();
    TSTAMP(21);
    bar_sync<NB_PUB, 288>();
  }
  TSTAMP(22);

  if (p == 0 && b < N_FFN) {
    uint32_t wf[20][4], m[6][4];
    mbar_wait(bar + 8 * B_FFN, 1);
#pragma unroll
    for (int i = 0; i < 20; ++i)
      ldsm4t(wf[i], sb + OFF_FFN + (lane & 8) * 2560 + (80 * wq + 8 * (lane >> 4) + (lane & 7)) * 64 + (((i & 3) ^ ((lane >> 1) & 3)) << 4) + 1024 * (i >> 2));
    TSTAMP(23);
    if (CAND_GAP) wait_until(clock32() + CAND_GAP);
    const uint32_t far = map_to_cta(sb, 0), dst = far + OFF_ACT + (4 * rank + wq) * 128 + gq * 16, step = map_to_cta(sb, 1) - far;
    gather_lazy<6, 64 * BOX, 8, 0>(m, at<16>(P.sc + M_CAND, (8 * (gq & 6) + 8 * rank + 2 * wq) * BOX + (lane & 7)), ep, budget);
    TSTAMP(24);
    const bool second = m[5][2] > m[4][2];
    const uint32_t wtok = ~__reduce_max_sync(0xFFFFFFFFu, max(m[4][2], m[5][2]));
    float f[4][4];
#pragma unroll
    for (int s = 0; s < 5; ++s) {
      const uint32_t b0 = second ? m[(s & 6) + 1][2 * (s & 1)] : m[s & 6][2 * (s & 1)], b1 = second ? m[(s & 6) + 1][2 * (s & 1) + 1] : m[s & 6][2 * (s & 1) + 1];
#pragma unroll
      for (int mt = 0; mt < 4; ++mt) mma16(f[mt], wf[4 * s + mt], b0, b1, s ? f[mt] : z4);
    }
    if (t == ((wtok >> 8) & 3)) {
      const bool e = wtok & 1;
#pragma unroll
      for (int r = 0; r < 2; ++r)
        asm volatile("st.async.weak.shared::cluster.mbarrier::complete_tx::bytes.v4.f32 [%0], {%1, %2, %3, %4}, [%5];"
                     ::"r"(dst + r * step), "f"(e ? f[2 * r][1] : f[2 * r][0]), "f"(e ? f[2 * r][3] : f[2 * r][2]),
                       "f"(e ? f[2 * r + 1][1] : f[2 * r + 1][0]), "f"(e ? f[2 * r + 1][3] : f[2 * r + 1][2]), "r"(far + r * step + (OFF_BAR + 8 * B_ACT)) : "memory");
    }
    __syncwarp();
    if (warp == 0) {
      sts1(sb + OFF_KEY + 80, ~wtok);
      if (b < 80) bar_arrive<NB_WIN, 64>();
    }
    TSTAMP(25);
  }
  {
    const uint32_t n0 = __shfl_sync(0xFFFFFFFFu, nw, 2 * gq), n1 = __shfl_sync(0xFFFFFFFFu, nw, 2 * gq + 16);
    nrm[0] = dup_hi(n0); nrm[1] = dup_hi(n1); nrm[2] = dup_lo(n0); nrm[3] = dup_lo(n1);
#pragma unroll
    for (int k = 0; k < 20; ++k) {
      uint32_t& x = xr[k >> 2][k & 3];
      acc2(x, gb[k >> 1], fma2(fma2(x, nrm[k & 1], nrm[2 + (k & 1)]), c1[k >> 1], sv[k >> 1]));
    }
  }
#pragma unroll
  for (int s5 = 0; s5 < 5; ++s5) stsm4(xt + trow * 160 + (OFF_OUT + 32 * s5), xr[s5]);
  asm volatile("fence.proxy.async.shared::cta;" ::: "memory");
  asm volatile("bar.arrive %0, 160;" ::"r"(turn + (NB_OUT - NB_TURN)) : "memory");
  if (p == 1 && b < N_FFN) {
    const uint32_t kr = ((lane & 7) >> 1) + 4 * (lane >> 4) + 8 * (lane & 1);
    uint32_t wd[10][4];
    mbar_wait(bar + 8 * B_XS, 0);
#pragma unroll
    for (int i = 0; i < 10; ++i) ldsm4t(wd[i], sb + OFF_FFN + 40960 + kr * 128 + (((2 * wq + ((lane >> 3) & 1)) ^ (kr & 7)) << 4) + 2048 * i);
    TSTAMP(23);
    uint4* const ydst = at<16>(P.sc + M_YP, ((b & ~3) + wq) * BOX + 4 * (gq & 6) + 2 * (b & 3) + (gq & 1));
    mbar_wait(bar + 8 * B_ACT, 1);
    TSTAMP(24);
    float v[8];
#pragma unroll
    for (int i = 0; i < 8; ++i) v[i] = f32(lds1(sb + OFF_ACT + 128 * i + 4 * lane));
    const float gu = bf_round(((v[0] + v[1]) + (v[2] + v[3])) + ((v[4] + v[5]) + (v[6] + v[7])));
    const float a = bf_round(gu * sigmoid(gu)) * shx(gu, 1);
    const uint32_t aw = pack2(a, shx(a, 2));
    const uint32_t b0 = __shfl_sync(0xFFFFFFFFu, aw, 4 * t), b1 = __shfl_sync(0xFFFFFFFFu, aw, 4 * t + 16);
    const bool odd = gq & 1;
    float y[5][4];
#pragma unroll
    for (int q = 0; q < 5; ++q) mma16(y[q], wd[2 * q], odd ? 0u : b0, odd ? 0u : b1, z4);
#pragma unroll
    for (int q = 0; q < 5; ++q) mma16(y[q], wd[2 * q + 1], odd ? b0 : 0u, odd ? b1 : 0u, y[q]);
    uint32_t w[4];
#pragma unroll
    for (int e = 0; e < 4; ++e) w[e] = u32(t & 2 ? (t & 1 ? y[3][e] : y[2][e]) : (t & 1 ? y[1][e] : y[0][e]));
    st_rlx4(ydst + 32 * t, tag(w[0], ep), w[1], w[2], w[3]);
    if (t == 0) st_rlx4(ydst + 128, tag(u32(y[4][0]), ep), u32(y[4][1]), u32(y[4][2]), u32(y[4][3]));
    __syncwarp();
    if (warp == 4 && b < 80) bar_arrive<NB_YP, 64>();
    TSTAMP(25);
  }
}

__global__ void __cluster_dims__(2, 1, 1) __launch_bounds__(384, 1) fused_block_kernel(const __grid_constant__ Params P) {
  extern __shared__ __align__(1024) uint8_t sm[];
  const uint32_t sb = (uint32_t)__cvta_generic_to_shared(sm), t0 = clock32();
  const int tid = threadIdx.x, lane = tid & 31;
  uint32_t key = blockIdx.x;
  asm("mov.u32 %0, %%smid;" : "=r"(key));
  const __nv_bfloat16* wmod = (&P.wmod)[tid >> 9];
  asm volatile("" : "+l"(wmod));
  const int warp = __shfl_sync(0xFFFFFFFFu, tid >> 5, 0), c = key >> 1, rank = blockIdx.x & 1;
  const uint32_t bar = sb + OFF_BAR;
  const auto role = [&]() {
    const int q7 = ((c - 32) * 37) >> 8;
    return 2 * pick(c < 32, 8 * (c & 7) + (c >> 3), pick(c < 60, 8 * c - 55 * q7 - 244, c - 58)) + rank;
  };
  const bool spare = BY_SM && (c >> 1) == 30;
  int budget = SPIN_LIMIT, b;
  uint32_t e0 = 0;
  if (warp == 11) {
    if (elect_one()) {
#pragma unroll
      for (int i = 0; i < 12; ++i) mbar_init(bar + 8 * i, i == B_TAB ? 96 : i == B_HALO ? 8 : (i >> 2) == 1 ? 16 : 1);
      asm volatile("fence.mbarrier_init.release.cluster;" ::: "memory");
    }
    __syncwarp();
    asm volatile("barrier.cluster.arrive.relaxed.aligned;" ::: "memory");
    b = role();
    if (spare) {
      wait_until(t0 + 4000);
      return;
    }
    TSTAMP(27);
    const int g = (b >> 1) & 7;
    if (elect_one()) {
      mbar_expect_tx(bar + 8 * B_FULL, STAGE);
      tma2(sb, &P.xa, bar + 8 * B_FULL, 640 * rank, 128 * (b >> 4));
    }
    asm volatile("barrier.cluster.wait.aligned;" ::: "memory");
    if (elect_one()) {
      tma3_both(sb + STAGE_A + rank * (STAGE_B0 / 2), &P.w0, bar + 8 * B_FULL, 80 * g, 32 * rank, 0);
      tma3_both(sb + STAGE_A + STAGE_B0 + rank * (STAGE_B1 / 2), &P.w1, bar + 8 * B_FULL, 80 * g + 64, 32 * rank, 0);
    }
    TSTAMP(28);
    st_rlx1(at<4>(P.sc + M_ST1, b * (4 * BOX) + lane), 0u);
    __syncwarp();
    if (lane == 0) mbar_arrive(bar + 8 * B_XS);
  } else {
    asm volatile("barrier.cluster.arrive.relaxed.aligned;" ::: "memory");
    const int u = (c & 48) + 2 * (c & 7) + ((c >> 3) & 1) - (c & 32 ? c & 7 : 0), kb = 2 * u + rank;
    const bool gemv = warp < 10 && c < 40;
    uint32_t cv = 0;
    if (gemv) {
      const __nv_bfloat16* src = at<16>(wmod, (320 * rank + (tid >> 2)) * 480 + 4 * u + (tid & 3));
      const uint32_t dst = sb + 3 * STAGE + 16 * (tid ^ ((tid >> 3) & 3));
#pragma unroll
      for (int i = 0; i < 4; ++i)
        asm volatile("cp.async.cg.shared.global.L2::128B [%0], [%1], 16;" ::"r"(dst + 5120 * i), "l"(src + i * 80 * 3840) : "memory");
    } else if (warp == 10 && elect_one()) {
      asm volatile("prefetch.tensormap [%0];" ::"l"(&P.xa) : "memory");
      asm volatile("prefetch.tensormap [%0];" ::"l"(&P.w0) : "memory");
      asm volatile("prefetch.tensormap [%0];" ::"l"(&P.w1) : "memory");
    }
    TSTAMP(26);
    asm volatile("barrier.cluster.wait.aligned;" ::: "memory");
    if (spare) return;
    if (gemv) asm volatile("ld.global.nc.u16 %0, [%1];" : "=r"(cv) : "l"(at<2>(P.c, 320 * rank + 10 * (tid & 24) + ((tid >> 2) & ~7) + (tid & 7))));
    b = role();
    uint4* const box = P.sc + b * BOX;
    e0 = ld_rlx1(at<4>(box + M_EPOCH, lane));
    asm volatile("cp.async.commit_group;" ::: "memory");
    if (warp < 8) {
      const __nv_bfloat16* src = at<16>(P.x, (16 * b + (tid >> 4)) * 80 + (tid & 15));
      wait_until(t0 + XS_AT);
#pragma unroll
      for (int i = 0; i < 5; ++i)
        asm volatile("cp.async.cg.shared.global [%0], [%1], 16;" ::"r"(sb + OFF_XS + 4096 * i + 16 * tid), "l"(src + 128 * i) : "memory");
    }
    if (warp == 10) {
      uint4* const dst = at<16>(P.sc + TABLES, 80 * (lane & 28) + 4 * kb + (lane & 3));
      if (c < 40) st_rlx4(dst, 0u, 0u, 0u, 0u);
      if (lane == 0) mbar_expect_tx(bar + 8 * B_GO, c < 40 ? 1280 : 0);
      TALIGN(0);
      if (c < 40) {
        const uint32_t ep = next_epoch(e0);
        mbar_wait(bar + 8 * B_GO, 0);
        TSTAMP(1);
        float v[10];
#pragma unroll
        for (int i = 0; i < 10; ++i) v[i] = f32(lds1(sb + OFF_RED + 128 * i + 4 * lane));
        float s = ((v[0] + v[1]) + (v[2] + v[3])) + ((v[4] + v[5]) + (v[6] + v[7])) + (v[8] + v[9]);
        s += shx(s, 16);
        const uint32_t w = fma2(pack2(s, shx(s, 1)), 0x3F803F80u, kb < 40 ? 0u : 0x3F803F80u);
        st_rlx4(dst, __shfl_sync(0xFFFFFFFFu, w, 2 * (lane & 3)), __shfl_sync(0xFFFFFFFFu, w, 2 * (lane & 3) + 8), ep, ep);
        TSTAMP(2);
      }
    } else if (gemv) {
      const float x = bf_lo(cv), s = x * sigmoid(x);
      const uint32_t sw = pack2(s, shx(s, 1));
      uint32_t bw[4], a[4][4];
#pragma unroll
      for (int i = 0; i < 4; ++i) bw[i] = __shfl_sync(0xFFFFFFFFu, sw, 8 * i + 2 * (lane & 3));
      const uint32_t far = map_to_cta(sb, (lane >> 1) & 1), dst = far + OFF_RED + 128 * warp + 64 * rank + 32 * (lane & 1) + (lane & 28);
      const uint32_t la = sb + 3 * STAGE + 512 * warp + (lane >> 4) * 5120 + (lane & 7) * 64 + ((((lane >> 3) & 1) ^ ((lane >> 1) & 3)) << 4);
      sched_fence(P.zero);
      asm volatile("cp.async.wait_group 0;" ::: "memory");
      __syncwarp();
      TSTAMP(28);
#pragma unroll
      for (int i = 0; i < 4; ++i) ldsm4t(a[i], (la ^ (32 * (i & 1))) + (i >> 1) * 10240);
      float d[2][4];
      const float z4[4] = {0.f, 0.f, 0.f, 0.f};
#pragma unroll
      for (int i = 0; i < 4; ++i) mma16(d[i & 1], a[i], bw[i & 2], bw[(i & 2) + 1], i < 2 ? z4 : d[i & 1]);
      const float v = lane & 2 ? (lane & 1 ? d[1][2] : d[1][0]) : (lane & 1 ? d[0][2] : d[0][0]);
      asm volatile("st.async.weak.shared::cluster.mbarrier::complete_tx::bytes.f32 [%0], %1, [%2];" ::"r"(dst), "f"(v), "r"(far + OFF_BAR + 8 * B_GO) : "memory");
      TSTAMP(1);
    }
  }
  if (warp >= 8) {
    asm volatile("setmaxnreg.dec.sync.aligned.u32 56;");
    if (warp == 11) {
      wait_until(t0 + S_GAP);
      run_producer(P, sm, sb, b, t0);
    } else {
      run_helper(P, sm, sb, b, warp - 8, next_epoch(e0), budget, t0 + POLL_AT);
    }
    TDUMP();
  } else {
    run_consumer(P, sm, sb, b, warp, next_epoch(e0), budget);
    TDUMP();
  }
}

typedef CUresult (*EncodeFn)(CUtensorMap*, CUtensorMapDataType, cuuint32_t, void*, const cuuint64_t*, const cuuint64_t*, const cuuint32_t*,
                             const cuuint32_t*, CUtensorMapInterleave, CUtensorMapSwizzle, CUtensorMapL2promotion, CUtensorMapFloatOOBfill);

void encode(EncodeFn fn, CUtensorMap* m, const void* base, int rank, const cuuint64_t* dims, const cuuint64_t* strides, const cuuint32_t* box,
            CUtensorMapSwizzle sw) {
  const cuuint32_t es[3] = {1, 1, 1};
  fn(m, CU_TENSOR_MAP_DATA_TYPE_BFLOAT16, rank, const_cast<void*>(base), dims, strides, box, es, CU_TENSOR_MAP_INTERLEAVE_NONE, sw,
     CU_TENSOR_MAP_L2_PROMOTION_L2_128B, CU_TENSOR_MAP_FLOAT_OOB_FILL_NONE);
}

}

extern "C" void kernel_launch(void* const* d_in, const int* in_sizes, int n_in, void* d_out, int out_size) {
  (void)in_sizes; (void)n_in; (void)out_size;
  static EncodeFn fn = nullptr;
  static void* scratch = nullptr;
  if (!fn) {
    void* f = nullptr;
    cudaDriverEntryPointQueryResult q;
    cudaGetDriverEntryPoint("cuTensorMapEncodeTiled", &f, cudaEnableDefault, &q);
    fn = (EncodeFn)f;
    cudaFuncSetAttribute(fused_block_kernel, cudaFuncAttributeMaxDynamicSharedMemorySize, SMEM_BYTES);
    cudaGetSymbolAddress(&scratch, g_scratch);
  }
  Params P;
  P.sc = (uint4*)scratch;
  P.zero = 0;
  const cuuint64_t xd[2] = {1280, 1024}, xs[1] = {2560};
  const cuuint32_t xb[2] = {64, 128};
  encode(fn, &P.xa, d_in[0], 2, xd, xs, xb, CU_TENSOR_MAP_SWIZZLE_128B);
  const cuuint32_t ob[2] = {80, 16};
  encode(fn, &P.om, d_out, 2, xd, xs, ob, CU_TENSOR_MAP_SWIZZLE_NONE);
  const cuuint64_t wd3[3] = {640, 640, 3}, ws3[2] = {3840, 1280};
  const cuuint32_t w0b[3] = {64, 32, 3}, w1b[3] = {16, 32, 3};
  encode(fn, &P.w0, d_in[1], 3, wd3, ws3, w0b, CU_TENSOR_MAP_SWIZZLE_128B);
  encode(fn, &P.w1, d_in[1], 3, wd3, ws3, w1b, CU_TENSOR_MAP_SWIZZLE_32B);
  const cuuint64_t md[2] = {3840, 640}, ms[1] = {7680};
  const cuuint32_t mb0[2] = {64, 160}, mb1[2] = {16, 160};
  encode(fn, &P.wm0, d_in[9], 2, md, ms, mb0, CU_TENSOR_MAP_SWIZZLE_128B);
  encode(fn, &P.wm1, d_in[9], 2, md, ms, mb1, CU_TENSOR_MAP_SWIZZLE_32B);
  const cuuint64_t od3[3] = {608, 640, 2}, os3[2] = {1280, 64}, od2[2] = {640, 640}, os2[1] = {1280};
  const cuuint32_t oab[3] = {32, 80, 2}, obb[2] = {16, 80};
  encode(fn, &P.woa, d_in[2], 3, od3, os3, oab, CU_TENSOR_MAP_SWIZZLE_64B);
  encode(fn, &P.wob, d_in[2], 2, od2, os2, obb, CU_TENSOR_MAP_SWIZZLE_64B);
  const cuuint64_t gd[3] = {1728, 160, 4}, gs[2] = {3456, 160 * 3456}, dd[3] = {64, 1728, 10}, ds[2] = {1280, 128};
  const cuuint32_t gb[3] = {32, 160, 1}, db[3] = {64, 16, 5};
  encode(fn, &P.wg, d_in[5], 3, gd, gs, gb, CU_TENSOR_MAP_SWIZZLE_64B);
  encode(fn, &P.wu, d_in[6], 3, gd, gs, gb, CU_TENSOR_MAP_SWIZZLE_64B);
  encode(fn, &P.wd, d_in[7], 3, dd, ds, db, CU_TENSOR_MAP_SWIZZLE_128B);
  P.x = (const __nv_bfloat16*)d_in[0];
  P.wqkv = (const __nv_bfloat16*)d_in[1];
  P.wr = (const __nv_bfloat16*)d_in[4];
  P.wo = (const __nv_bfloat16*)d_in[2];
  P.wgate = (const __nv_bfloat16*)d_in[5];
  P.wup = (const __nv_bfloat16*)d_in[6];
  P.wdown = (const __nv_bfloat16*)d_in[7];
  P.c = (const __nv_bfloat16*)d_in[8];
  P.wmod = (const __nv_bfloat16*)d_in[9];
  P.out = (__nv_bfloat16*)d_out;
  fused_block_kernel<<<BY_SM ? 132 : 128, 384, SMEM_BYTES>>>(P);
}
```

```cpp
#include <cuda_runtime.h>
#include <cuda.h>
#include <cuda_bf16.h>
#include <stdint.h>

namespace {

constexpr int STAGE_A = 16384, STAGE_B0 = 24576, STAGE_B1 = 6144, STAGE = STAGE_A + STAGE_B0 + STAGE_B1;
constexpr int WO = 15360;
constexpr int OFF_FFN = 4 * WO, OFF_LM = 2 * STAGE, OFF_X2 = 4 * STAGE, OFF_OUT = 0;
constexpr int OFF_H = 4 * STAGE, OFF_L = OFF_H + 9 * 2560, OFF_XS = OFF_H, OFF_RED = OFF_L, OFF_SINK = OFF_L + 10240;
constexpr int OFF_C1 = 225280, OFF_ACT = OFF_C1, OFF_ROWS = OFF_C1 + 1024, OFF_PRM = OFF_C1 + 2560, OFF_SILU = OFF_PRM + 1600;
constexpr int OFF_KEY = OFF_SILU + 320, OFF_BAR = OFF_KEY + 128, OFF_TIME = OFF_BAR + 256, SMEM_BYTES = OFF_TIME + 1536;
static_assert(OFF_H % 512 == 0, "lane bits of the halo address");
static_assert(SMEM_BYTES <= 232448 && OFF_BAR % 64 == 0, "smem");
enum { R_GA = 0, R_SB = 160, R_C1 = 320, R_GB = 480, R_FIN = 640, R_P = 800 + R_C1, R_ONE = 704 };

enum { B_FULL = 0, B_EMPTY = 4, B_HALO = 8, B_TAB = 9, B_GO = 10, B_XS = 11, B_ACT = B_FULL, B_FFN = B_FULL + 1, B_WO0 = B_FULL + 2, B_WO1 = B_FULL + 3 };
enum { NB_PV = 1, NB_TURN = 2, NB_KEY = 4, NB_REDO = 5, NB_HELP = 6, NB_HALO = 7, NB_PUB = 8, NB_GO = 9, NB_LM = 10, NB_OUT = 11, NB_WIN = 13, NB_YP = 14 };

enum { M_EARLY = 0, M_ST1 = 32, M_EPOCH = 40, M_HALO = 48, M_ST2 = 208, M_CAND = 336, M_LATE = 368, M_YP = 400, M_O = 560, BOX = 1840 };
constexpr int TABLES = 128 * BOX;
__device__ uint4 g_scratch[TABLES + 8 * 320];

constexpr int N_FFN = 108;
constexpr uint32_t SMEM_BASE = 1024;
#define AHEAD 1
#define FORCE_REDO 0
#define FFN_EARLY 0
#define DOWN_GAP 1900
#define NO_BY_SM 0
#define NAP 20
#define XS_AT 900
#define S_GAP 1300
#define POLL_AT 4000
#define WPF_AT 4500
#define LMPF_AT 4
#define TOUCH_AT 1000
#define TOUCH_GAP 1100
#define HALO_GAP 400
#define LATE_GAP 800
#define FGO_STEP 4
#define FFN_GAP 0
#define OUT_AT 400
#define OUT_GAP 0
#define YP_GAP 250
#define PASS1 5
#define PASS0 2
#define PASS_AT 3
constexpr int SPIN_LIMIT = 1 << 16;

struct Params {
  const __nv_bfloat16 *wmod, *c, *x;
  uint4* sc;
  uint32_t zero;
  const __nv_bfloat16 *wqkv, *wr, *wo, *wgate, *wup, *wdown;
  __nv_bfloat16* out;
  CUtensorMap xa, w0, w1, wm0, wm1, woa, wob, wg, wu, wd, om;
};

__device__ __forceinline__ uint32_t clock32() {
  uint32_t c;
  asm volatile("mov.u32 %0, %%clock;" : "=r"(c));
  return c;
}
#define TSTAMP(i) do { } while (0)
#define TDUMP() do { } while (0)
#define TALIGN(k) do { } while (0)

__device__ __forceinline__ void mbar_init(uint32_t b, uint32_t c) { asm volatile("mbarrier.init.shared::cta.b64 [%0], %1;" ::"r"(b), "r"(c) : "memory"); }
__device__ __forceinline__ void mbar_expect_tx(uint32_t b, uint32_t n) { asm volatile("mbarrier.arrive.expect_tx.shared::cta.b64 _, [%0], %1;" ::"r"(b), "r"(n) : "memory"); }
__device__ __forceinline__ void mbar_arrive(uint32_t b) { asm volatile("mbarrier.arrive.shared::cta.b64 _, [%0];" ::"r"(b) : "memory"); }
__device__ __forceinline__ uint32_t map_to_cta(uint32_t a, uint32_t rank) {
  uint32_t r;
  asm("mapa.shared::cluster.u32 %0, %1, %2;" : "=r"(r) : "r"(a), "r"(rank));
  return r;
}
__device__ __forceinline__ void mbar_arrive_cluster(uint32_t b) { asm volatile("mbarrier.arrive.shared::cluster.b64 _, [%0];" ::"r"(b) : "memory"); }
__device__ __forceinline__ void mbar_wait(uint32_t b, uint32_t ph) {
  asm volatile("{.reg .pred p;\n"
               "RETRY: mbarrier.try_wait.parity.shared::cta.b64 p, [%0], %1;\n"
               "@!p bra RETRY;}" ::"r"(b), "r"(ph) : "memory");
}
__device__ __forceinline__ bool elect_one() {
  uint32_t r;
  asm volatile("{.reg .pred p; elect.sync _|p, 0xFFFFFFFF; selp.u32 %0, 1, 0, p;}" : "=r"(r));
  return r;
}
template <int ID, int N> __device__ __forceinline__ void bar_sync() { asm volatile("bar.sync %0, %1;" ::"n"(ID), "n"(N) : "memory"); }
template <int ID, int N> __device__ __forceinline__ void bar_arrive() { asm volatile("bar.arrive %0, %1;" ::"n"(ID), "n"(N) : "memory"); }
__device__ __forceinline__ void turn_wait(uint32_t id) { asm volatile("bar.sync %0, 256;" ::"r"(id) : "memory"); }
__device__ __forceinline__ void turn_pass(uint32_t id) { asm volatile("bar.arrive %0, 256;" ::"r"(id) : "memory"); }
__device__ __forceinline__ void tma2(uint32_t dst, const CUtensorMap* m, uint32_t bar, int c0, int c1) {
  asm volatile("cp.async.bulk.tensor.2d.shared::cluster.global.mbarrier::complete_tx::bytes [%0], [%1, {%3, %4}], [%2];" ::"r"(dst), "l"(m), "r"(bar), "r"(c0), "r"(c1) : "memory");
}
__device__ __forceinline__ void tma3(uint32_t dst, const CUtensorMap* m, uint32_t bar, int c0, int c1, int c2) {
  asm volatile("cp.async.bulk.tensor.3d.shared::cluster.global.mbarrier::complete_tx::bytes [%0], [%1, {%3, %4, %5}], [%2];" ::"r"(dst), "l"(m), "r"(bar), "r"(c0), "r"(c1), "r"(c2) : "memory");
}
__device__ __forceinline__ void tma2_both(uint32_t dst, const CUtensorMap* m, uint32_t bar, int c0, int c1) {
  asm volatile("cp.async.bulk.tensor.2d.shared::cluster.global.mbarrier::complete_tx::bytes.multicast::cluster [%0], [%1, {%3, %4}], [%2], %5;"
               ::"r"(dst), "l"(m), "r"(bar), "r"(c0), "r"(c1), "h"((uint16_t)3) : "memory");
}
__device__ __forceinline__ void tma3_both(uint32_t dst, const CUtensorMap* m, uint32_t bar, int c0, int c1, int c2) {
  asm volatile("cp.async.bulk.tensor.3d.shared::cluster.global.mbarrier::complete_tx::bytes.multicast::cluster [%0], [%1, {%3, %4, %5}], [%2], %6;"
               ::"r"(dst), "l"(m), "r"(bar), "r"(c0), "r"(c1), "r"(c2), "h"((uint16_t)3) : "memory");
}
__device__ __forceinline__ void bulk_prefetch(const void* src, uint32_t bytes) {
  asm volatile("cp.async.bulk.prefetch.L2.global [%0], %1;" ::"l"(src), "r"(bytes) : "memory");
}
__device__ __forceinline__ void wg_fence() { asm volatile("wgmma.fence.sync.aligned;" ::: "memory"); }
__device__ __forceinline__ void wg_commit() { asm volatile("wgmma.commit_group.sync.aligned;" ::: "memory"); }
__device__ __forceinline__ void wg_wait() { asm volatile("wgmma.wait_group.sync.aligned 0;" ::: "memory"); }
__device__ __forceinline__ constexpr uint64_t make_desc(uint32_t addr, uint32_t lbo, uint32_t sbo, uint32_t mode) {
  return (uint64_t)((addr & 0x3FFFF) >> 4) | ((uint64_t)(lbo >> 4) << 16) | ((uint64_t)(sbo >> 4) << 32) | ((uint64_t)mode << 62);
}
__device__ __forceinline__ void ldsm4(uint32_t& r0, uint32_t& r1, uint32_t& r2, uint32_t& r3, uint32_t a) {
  asm volatile("ldmatrix.sync.aligned.m8n8.x4.shared.b16 {%0, %1, %2, %3}, [%4];" : "=r"(r0), "=r"(r1), "=r"(r2), "=r"(r3) : "r"(a) : "memory");
}
__device__ __forceinline__ void ldsm4(uint32_t* r, uint32_t a) { ldsm4(r[0], r[1], r[2], r[3], a); }
__device__ __forceinline__ void ldsm2(uint32_t* r, uint32_t a) {
  asm volatile("ldmatrix.sync.aligned.m8n8.x2.shared.b16 {%0, %1}, [%2];" : "=r"(r[0]), "=r"(r[1]) : "r"(a) : "memory");
}
__device__ __forceinline__ void ldsm4t(uint32_t* r, uint32_t a) {
  asm volatile("ldmatrix.sync.aligned.m8n8.x4.trans.shared.b16 {%0, %1, %2, %3}, [%4];" : "=r"(r[0]), "=r"(r[1]), "=r"(r[2]), "=r"(r[3]) : "r"(a) : "memory");
}
__device__ __forceinline__ void ldsm2t(uint32_t* r, uint32_t a) {
  asm volatile("ldmatrix.sync.aligned.m8n8.x2.trans.shared.b16 {%0, %1}, [%2];" : "=r"(r[0]), "=r"(r[1]) : "r"(a) : "memory");
}
__device__ __forceinline__ void ld_row(uint32_t (&r)[10], uint32_t a) {
  ldsm4(r, a);
  ldsm4(r + 4, a + 64);
  ldsm2(r + 8, a + 128);
}
__device__ __forceinline__ void stsm4(uint32_t a, const uint32_t* r) {
  asm volatile("stmatrix.sync.aligned.m8n8.x4.shared.b16 [%0], {%1, %2, %3, %4};" ::"r"(a), "r"(r[0]), "r"(r[1]), "r"(r[2]), "r"(r[3]) : "memory");
}
__device__ __forceinline__ void stsm2(uint32_t a, const uint32_t* r) {
  asm volatile("stmatrix.sync.aligned.m8n8.x2.shared.b16 [%0], {%1, %2};" ::"r"(a), "r"(r[0]), "r"(r[1]) : "memory");
}
__device__ __forceinline__ void lds4(uint32_t* r, uint32_t a) {
  asm volatile("ld.shared.v4.u32 {%0, %1, %2, %3}, [%4];" : "=r"(r[0]), "=r"(r[1]), "=r"(r[2]), "=r"(r[3]) : "r"(a) : "memory");
}
__device__ __forceinline__ uint32_t lds1(uint32_t a) {
  uint32_t v;
  asm volatile("ld.shared.u32 %0, [%1];" : "=r"(v) : "r"(a) : "memory");
  return v;
}
__device__ __forceinline__ void sts1(uint32_t a, uint32_t v) { asm volatile("st.shared.u32 [%0], %1;" ::"r"(a), "r"(v) : "memory"); }
__device__ __forceinline__ void sts2(uint32_t a, uint32_t v0, uint32_t v1) { asm volatile("st.shared.v2.u32 [%0], {%1, %2};" ::"r"(a), "r"(v0), "r"(v1) : "memory"); }
__device__ __forceinline__ void mma16(float (&d)[4], uint32_t a0, uint32_t a1, uint32_t a2, uint32_t a3, uint32_t b0, uint32_t b1, const float* c) {
  asm volatile("mma.sync.aligned.m16n8k16.row.col.f32.bf16.bf16.f32 {%0, %1, %2, %3}, {%4, %5, %6, %7}, {%8, %9}, {%10, %11, %12, %13};"
               : "=f"(d[0]), "=f"(d[1]), "=f"(d[2]), "=f"(d[3])
               : "r"(a0), "r"(a1), "r"(a2), "r"(a3), "r"(b0), "r"(b1), "f"(c[0]), "f"(c[1]), "f"(c[2]), "f"(c[3]));
}
__device__ __forceinline__ void mma16(float (&d)[4], const uint32_t* a, uint32_t b0, uint32_t b1, const float* c) { mma16(d, a[0], a[1], a[2], a[3], b0, b1, c); }
__device__ __forceinline__ void mma8(float (&d)[4], uint32_t a0, uint32_t a1, uint32_t b0, const float* c) {
  asm volatile("mma.sync.aligned.m16n8k8.row.col.f32.bf16.bf16.f32 {%0, %1, %2, %3}, {%4, %5}, {%6}, {%7, %8, %9, %10};"
               : "=f"(d[0]), "=f"(d[1]), "=f"(d[2]), "=f"(d[3]) : "r"(a0), "r"(a1), "r"(b0), "f"(c[0]), "f"(c[1]), "f"(c[2]), "f"(c[3]));
}
__device__ __forceinline__ uint32_t pack2(float lo, float hi) {
  uint32_t r;
  asm volatile("cvt.rn.bf16x2.f32 %0, %1, %2;" : "=r"(r) : "f"(hi), "f"(lo));
  return r;
}
__device__ __forceinline__ float bf_lo(uint32_t w) { return __uint_as_float(w << 16); }
__device__ __forceinline__ float bf_hi(uint32_t w) { return __uint_as_float(w & 0xFFFF0000u); }
__device__ __forceinline__ float bf_round(float v) { return __uint_as_float(pack2(0.f, v)); }
__device__ __forceinline__ uint32_t fma2(uint32_t a, uint32_t b, uint32_t c) {
  uint32_t r;
  asm("fma.rn.bf16x2 %0, %1, %2, %3;" : "=r"(r) : "r"(a), "r"(b), "r"(c));
  return r;
}
__device__ __forceinline__ void acc2(uint32_t& c, uint32_t a, uint32_t b) { asm("fma.rn.bf16x2 %0, %1, %2, %0;" : "+r"(c) : "r"(a), "r"(b)); }
__device__ __forceinline__ float ex2(float v) {
  float r;
  asm("ex2.approx.ftz.f32 %0, %1;" : "=f"(r) : "f"(v));
  return r;
}
__device__ __forceinline__ float rcp(float v) {
  float r;
  asm("rcp.approx.ftz.f32 %0, %1;" : "=f"(r) : "f"(v));
  return r;
}
__device__ __forceinline__ float rsq(float v) {
  float r;
  asm("rsqrt.approx.ftz.f32 %0, %1;" : "=f"(r) : "f"(v));
  return r;
}
__device__ __forceinline__ float sigmoid(float v) { return rcp(1.f + ex2(v * -1.4426950408889634f)); }
__device__ __forceinline__ float f32(uint32_t v) { return __uint_as_float(v); }
__device__ __forceinline__ uint32_t u32(float v) { return __float_as_uint(v); }
__device__ __forceinline__ void ld_rlx4(uint32_t* v, const void* p) {
  asm volatile("{.reg .b128 q; ld.relaxed.gpu.global.b128 q, [%4]; mov.b128 {%0, %1, %2, %3}, q;}" : "=r"(v[0]), "=r"(v[1]), "=r"(v[2]), "=r"(v[3]) : "l"(p) : "memory");
}
__device__ __forceinline__ void ld_rlx2(uint32_t* v, const void* p) {
  asm volatile("{.reg .b64 q; ld.relaxed.gpu.global.b64 q, [%2]; mov.b64 {%0, %1}, q;}" : "=r"(v[0]), "=r"(v[1]) : "l"(p) : "memory");
}
__device__ __forceinline__ uint32_t ld_rlx1(const void* p) {
  uint32_t v;
  asm volatile("ld.relaxed.gpu.global.u32 %0, [%1];" : "=r"(v) : "l"(p) : "memory");
  return v;
}
__device__ __forceinline__ void st_rlx4(void* p, uint32_t a, uint32_t b, uint32_t c, uint32_t d) {
  asm volatile("{.reg .b128 q; mov.b128 q, {%1, %2, %3, %4}; st.relaxed.gpu.global.b128 [%0], q;}" ::"l"(p), "r"(a), "r"(b), "r"(c), "r"(d) : "memory");
}
__device__ __forceinline__ void st_rlx4(void* p, const uint32_t* v) { st_rlx4(p, v[0], v[1], v[2], v[3]); }
__device__ __forceinline__ void st_rlx2(void* p, uint32_t a, uint32_t b) { asm volatile("{.reg .b64 q; mov.b64 q, {%1, %2}; st.relaxed.gpu.global.b64 [%0], q;}" ::"l"(p), "r"(a), "r"(b) : "memory"); }
__device__ __forceinline__ void st_rlx1(void* p, uint32_t v) { asm volatile("st.relaxed.gpu.global.u32 [%0], %1;" ::"l"(p), "r"(v) : "memory"); }
template <int LUT> __device__ __forceinline__ uint32_t lop3(uint32_t a, uint32_t b, uint32_t c) {
  uint32_t r;
  asm volatile("lop3.b32 %0, %1, %2, %3, %4;" : "=r"(r) : "r"(a), "r"(b), "r"(c), "n"(LUT));
  return r;
}
__device__ __forceinline__ uint32_t tag(uint32_t w, uint32_t ep) { return lop3<0xD8>(w, ep, 1u); }
__device__ __forceinline__ uint32_t neq2(uint32_t a, uint32_t b, uint32_t e) { return lop3<0x7E>(a, b, e); }
__device__ __forceinline__ uint32_t next_epoch(uint32_t e) {
  asm volatile("add.u32 %0, %0, 1;" : "+r"(e));
  return e;
}
__device__ __forceinline__ void sched_fence(uint32_t zero) {
  asm volatile("{.reg .pred p; setp.ne.u32 p, %0, 0;\nSPIN: pmevent 0; @p bra.uni SPIN;}" ::"r"(zero) : "memory");
}
__device__ __forceinline__ int pick(bool c, int a, int b) {
  int r;
  asm("{.reg .pred p; setp.ne.u32 p, %1, 0; selp.b32 %0, %2, %3, p;}" : "=r"(r) : "r"((uint32_t)c), "r"(a), "r"(b));
  return r;
}
__device__ __forceinline__ uint32_t keep(uint32_t v) { return __shfl_xor_sync(0xFFFFFFFFu, v, 2); }
__device__ __forceinline__ void wait_until(uint32_t t) {
  while ((int)(clock32() - t) < 0) {
    asm volatile("nanosleep.u32 %0;" ::"n"(NAP));
  }
}
__device__ __forceinline__ float shx(float v, int o) { return __shfl_xor_sync(0xFFFFFFFFu, v, o); }
template <int SCALE, class T> __device__ __forceinline__ T* at(T* base, uint32_t i) {
  T* r;
  asm volatile("mad.wide.u32 %0, %1, %2, %3;" : "=l"(r) : "r"(i), "n"(SCALE), "l"(base));
  return r;
}
template <uint32_t MASK> __device__ __forceinline__ bool retry(uint32_t bad, int& budget) {
  uint32_t r;
  asm volatile("{.reg .pred p, q; .reg .b32 t; add.s32 %1, %1, -1; setp.gt.s32 q, %1, 0; and.b32 t, %2, %3; setp.ne.u32 p, t, 0;\n"
               "vote.sync.any.pred p, p, 0xFFFFFFFF; and.pred p, p, q; selp.u32 %0, 1, 0, p;}" : "=r"(r), "+r"(budget) : "r"(bad), "n"(MASK));
  return r;
}
template <int N, int W> __device__ __forceinline__ uint32_t stale(const uint32_t (*v)[4], uint32_t ep) {
  uint32_t bad = neq2(v[0][W], v[N > 1][W], ep);
#pragma unroll
  for (int i = 2; i < N; i += 2) bad |= neq2(v[i][W], v[i + 1 < N ? i + 1 : i][W], ep);
  return bad;
}
__device__ __forceinline__ void ld_rlx4_stale(uint32_t* v, const void* p, uint32_t w, uint32_t ep) {
  asm volatile("{.reg .b128 q; .reg .pred p; .reg .b32 t; lop3.b32 t, %5, %6, 1, 0x28; setp.ne.u32 p, t, 0; mov.b128 q, {%0, %1, %2, %3};\n"
               "@p ld.relaxed.gpu.global.b128 q, [%4]; mov.b128 {%0, %1, %2, %3}, q;}"
               : "+r"(v[0]), "+r"(v[1]), "+r"(v[2]), "+r"(v[3]) : "l"(p), "r"(w), "r"(ep) : "memory");
}
template <int N, int S0, int S1, int W> __device__ __forceinline__ void gather_lazy(uint32_t (*v)[4], const uint4* p, uint32_t ep, int& budget, bool skip_last = false) {
#pragma unroll
  for (int i = 0; i < 4 * N; ++i) {
    if ((i & 3) == W) v[i >> 2][W] = N == 7 && i >= 24 && skip_last ? ep & 1u : ~ep;
    else if (N == 7 && i >= 24) v[6][i & 3] = 0;
    else asm volatile("" : "=r"(v[i >> 2][i & 3]));
  }
#pragma unroll 1
  do {
#pragma unroll
    for (int i = 0; i < N; ++i) ld_rlx4_stale(v[i], p + (i & 1) * S0 + (i >> 1) * S1, v[i][W], ep);
  } while (retry<1>(stale<N, W>(v, ep), budget));
}
template <int N, int STRIDE, int W> __device__ __forceinline__ void gather(uint32_t (*v)[4], const uint4* p, uint32_t ep, int& budget) {
#pragma unroll 1
  do {
#pragma unroll
    for (int i = 0; i < N; ++i) ld_rlx4(v[i], p + i * STRIDE);
  } while (retry<1>(stale<N, W>(v, ep), budget));
}
__device__ __forceinline__ void row_stats(float (&s)[4], float& qlo, float& qhi, const uint32_t (&x)[5][4], const uint32_t (&b)[10], int gq) {
  const float z[4] = {0.f, 0.f, 0.f, 0.f};
  float q[4][4];
#pragma unroll
  for (int i = 0; i < 5; ++i) {
    mma16(s, x[i], b[2 * i], b[2 * i + 1], i ? s : z);
#pragma unroll
    for (int e = 0; e < 4; ++e) mma8(q[e], x[i][e & 2], x[i][(e & 2) + 1], x[i][e], i ? q[e] : z);
  }
  const bool odd = gq & 1;
  qlo = (odd ? q[0][1] : q[0][0]) + (odd ? q[2][1] : q[2][0]);
  qhi = (odd ? q[1][3] : q[1][2]) + (odd ? q[3][3] : q[3][2]);
}
__device__ __forceinline__ uint32_t norm_word(float s, float q, float& mean, float& rstd) {
  mean = s * (1.f / 640.f);
  rstd = rsq(fmaxf(fmaf(q, 1.f / 640.f, -mean * mean), 0.f) + 1e-5f);
  return pack2(-mean * bf_round(rstd), rstd);
}
__device__ __forceinline__ uint32_t dup_lo(uint32_t w) { return __byte_perm(w, 0u, 0x1010); }
__device__ __forceinline__ uint32_t dup_hi(uint32_t w) { return __byte_perm(w, 0u, 0x3232); }

__device__ __forceinline__ void wgmma_n192(float (&d)[96], const uint32_t (&a)[4], uint64_t db, int add) {
  asm volatile("{.reg .pred p; setp.ne.b32 p, %101, 0; wgmma.mma_async.sync.aligned.m64n192k16.f32.bf16.bf16 "
    "{%0, %1, %2, %3, %4, %5, %6, %7, %8, %9, %10, %11, %12, %13, %14, %15, "
    "%16, %17, %18, %19, %20, %21, %22, %23, %24, %25, %26, %27, %28, %29, %30, %31, "
    "%32, %33, %34, %35, %36, %37, %38, %39, %40, %41, %42, %43, %44, %45, %46, %47, "
    "%48, %49, %50, %51, %52, %53, %54, %55, %56, %57, %58, %59, %60, %61, %62, %63, "
    "%64, %65, %66, %67, %68, %69, %70, %71, %72, %73, %74, %75, %76, %77, %78, %79, "
    "%80, %81, %82, %83, %84, %85, %86, %87, %88, %89, %90, %91, %92, %93, %94, %95}, "
    "{%96, %97, %98, %99}, %100, p, 1, 1, 1;}"
    : "+f"(d[0]), "+f"(d[1]), "+f"(d[2]), "+f"(d[3]), "+f"(d[4]), "+f"(d[5]), "+f"(d[6]), "+f"(d[7]),
      "+f"(d[8]), "+f"(d[9]), "+f"(d[10]), "+f"(d[11]), "+f"(d[12]), "+f"(d[13]), "+f"(d[14]), "+f"(d[15]),
      "+f"(d[16]), "+f"(d[17]), "+f"(d[18]), "+f"(d[19]), "+f"(d[20]), "+f"(d[21]), "+f"(d[22]), "+f"(d[23]),
      "+f"(d[24]), "+f"(d[25]), "+f"(d[26]), "+f"(d[27]), "+f"(d[28]), "+f"(d[29]), "+f"(d[30]), "+f"(d[31]),
      "+f"(d[32]), "+f"(d[33]), "+f"(d[34]), "+f"(d[35]), "+f"(d[36]), "+f"(d[37]), "+f"(d[38]), "+f"(d[39]),
      "+f"(d[40]), "+f"(d[41]), "+f"(d[42]), "+f"(d[43]), "+f"(d[44]), "+f"(d[45]), "+f"(d[46]), "+f"(d[47]),
      "+f"(d[48]), "+f"(d[49]), "+f"(d[50]), "+f"(d[51]), "+f"(d[52]), "+f"(d[53]), "+f"(d[54]), "+f"(d[55]),
      "+f"(d[56]), "+f"(d[57]), "+f"(d[58]), "+f"(d[59]), "+f"(d[60]), "+f"(d[61]), "+f"(d[62]), "+f"(d[63]),
      "+f"(d[64]), "+f"(d[65]), "+f"(d[66]), "+f"(d[67]), "+f"(d[68]), "+f"(d[69]), "+f"(d[70]), "+f"(d[71]),
      "+f"(d[72]), "+f"(d[73]), "+f"(d[74]), "+f"(d[75]), "+f"(d[76]), "+f"(d[77]), "+f"(d[78]), "+f"(d[79]),
      "+f"(d[80]), "+f"(d[81]), "+f"(d[82]), "+f"(d[83]), "+f"(d[84]), "+f"(d[85]), "+f"(d[86]), "+f"(d[87]),
      "+f"(d[88]), "+f"(d[89]), "+f"(d[90]), "+f"(d[91]), "+f"(d[92]), "+f"(d[93]), "+f"(d[94]), "+f"(d[95])
    : "r"(a[0]), "r"(a[1]), "r"(a[2]), "r"(a[3]), "l"(db), "r"(add));
}
__device__ __forceinline__ void wgmma_n48(float (&d)[24], const uint32_t (&a)[4], uint64_t db, int add) {
  asm volatile("{.reg .pred p; setp.ne.b32 p, %29, 0; wgmma.mma_async.sync.aligned.m64n48k16.f32.bf16.bf16 "
    "{%0, %1, %2, %3, %4, %5, %6, %7, %8, %9, %10, %11, %12, %13, %14, %15, "
    "%16, %17, %18, %19, %20, %21, %22, %23}, "
    "{%24, %25, %26, %27}, %28, p, 1, 1, 1;}"
    : "+f"(d[0]), "+f"(d[1]), "+f"(d[2]), "+f"(d[3]), "+f"(d[4]), "+f"(d[5]), "+f"(d[6]), "+f"(d[7]),
      "+f"(d[8]), "+f"(d[9]), "+f"(d[10]), "+f"(d[11]), "+f"(d[12]), "+f"(d[13]), "+f"(d[14]), "+f"(d[15]),
      "+f"(d[16]), "+f"(d[17]), "+f"(d[18]), "+f"(d[19]), "+f"(d[20]), "+f"(d[21]), "+f"(d[22]), "+f"(d[23])
    : "r"(a[0]), "r"(a[1]), "r"(a[2]), "r"(a[3]), "l"(db), "r"(add));
}
__device__ __forceinline__ void wgmma_n80(float (&d)[40], const uint32_t (&a)[4], uint64_t db, int add) {
  asm volatile("{.reg .pred p; setp.ne.b32 p, %45, 0; wgmma.mma_async.sync.aligned.m64n80k16.f32.bf16.bf16 "
    "{%0, %1, %2, %3, %4, %5, %6, %7, %8, %9, %10, %11, %12, %13, %14, %15, "
    "%16, %17, %18, %19, %20, %21, %22, %23, %24, %25, %26, %27, %28, %29, %30, %31, "
    "%32, %33, %34, %35, %36, %37, %38, %39}, "
    "{%40, %41, %42, %43}, %44, p, 1, 1, 1;}"
    : "+f"(d[0]), "+f"(d[1]), "+f"(d[2]), "+f"(d[3]), "+f"(d[4]), "+f"(d[5]), "+f"(d[6]), "+f"(d[7]),
      "+f"(d[8]), "+f"(d[9]), "+f"(d[10]), "+f"(d[11]), "+f"(d[12]), "+f"(d[13]), "+f"(d[14]), "+f"(d[15]),
      "+f"(d[16]), "+f"(d[17]), "+f"(d[18]), "+f"(d[19]), "+f"(d[20]), "+f"(d[21]), "+f"(d[22]), "+f"(d[23]),
      "+f"(d[24]), "+f"(d[25]), "+f"(d[26]), "+f"(d[27]), "+f"(d[28]), "+f"(d[29]), "+f"(d[30]), "+f"(d[31]),
      "+f"(d[32]), "+f"(d[33]), "+f"(d[34]), "+f"(d[35]), "+f"(d[36]), "+f"(d[37]), "+f"(d[38]), "+f"(d[39])
    : "r"(a[0]), "r"(a[1]), "r"(a[2]), "r"(a[3]), "l"(db), "r"(add));
}

__device__ __forceinline__ constexpr int wo_off(int i) { return (i < 4 ? 8 + i : i - 4) * WO; }
__device__ __forceinline__ void load_stage(const Params& P, uint32_t sb, int st, int j, int g, int rank) {
  const uint32_t fb = sb + OFF_BAR + 8 * (B_FULL + (st & 3)), a = sb + (st & 3) * STAGE;
  mbar_expect_tx(fb, STAGE);
  tma2(a, &P.xa, fb, 640 * rank + 64 * st, 128 * j);
  tma3_both(a + STAGE_A + rank * (STAGE_B0 / 2), &P.w0, fb, 80 * g + 16 * (g & 1), 64 * st + 32 * rank, 0);
  tma3_both(a + STAGE_A + STAGE_B0 + rank * (STAGE_B1 / 2), &P.w1, fb, 80 * g + 64 * (~g & 1), 64 * st + 32 * rank, 0);
}

__device__ __forceinline__ void run_producer(const Params& P, uint8_t* sm, uint32_t sb, int b, uint32_t t0) {
  const int rank = b & 1, g = (b >> 1) & 7, j = b >> 4;
  const uint32_t bar = sb + OFF_BAR;
#pragma unroll 1
  for (int st = 1; st < 10; ++st) {
    if (st == 2) {
      wait_until(t0 + WPF_AT);
      if (elect_one()) bulk_prefetch(P.wqkv + (128 + 4 * b) * 1920, 15360);
      bar_sync<NB_GO, 160>();
    }
    if (st == 9) bar_sync<NB_HELP, 128>();
    mbar_wait(bar + 8 * (B_EMPTY + (st & 3)), (((st + 1) >> 2) + 1) & 1);
    if (elect_one()) {
      load_stage(P, sb, st, j, g, rank);
      const int k = st - LMPF_AT;
      if ((uint32_t)k < 5u) bulk_prefetch(P.wmod + (5 * b + k) * 3840 + 1280, 5120);
      if (st == 7) bulk_prefetch(P.wo + b * 3200, 6400);
    }
  }
  TSTAMP(1);
#pragma unroll 1
  for (int i = 0; i < 8; ++i) {
    if (i < 2 || i == 4 || i == 7) mbar_wait(bar + 8 * (B_EMPTY + (i < 2 ? 2 + i : i & 1)), i == 0);
    if (elect_one()) {
      const uint32_t fb = bar + 8 * (i ? B_WO1 : B_WO0), a = sb + (i < 4 ? 8 + i : i - 4) * WO;
      if (i == 0) {
        mbar_expect_tx(bar + 8 * B_XS, 25600);
        tma2(sb + OFF_LM, &P.wm0, bar + 8 * B_XS, 1280 + 64 * (b & 31), 160 * (b >> 5));
        tma2(sb + OFF_LM + 20480, &P.wm1, bar + 8 * B_XS, 3328 + 16 * (b & 31), 160 * (b >> 5));
      }
      if (i < 2) mbar_expect_tx(fb, i ? 7 * 12800 : 12800);
      if ((i & 1) == rank) {
        const int k0 = 80 * (i ? i - (i <= g) : g);
        tma3_both(a, &P.woa, fb, 80 * g, k0, 0);
        tma2_both(a + 10240, &P.wob, fb, 80 * g + 64, k0);
      }
    }
  }
  TSTAMP(3);
  if (b < N_FFN) {
    if (elect_one()) {
      mbar_expect_tx(bar + 8 * B_ACT, 1024);
      mbar_expect_tx(bar + 8 * B_FFN, 40960);
    }
    uint32_t next = clock32();
#pragma unroll 1
    for (int i = 0; i < 6; ++i) {
      if (i == FFN_EARLY) {
        mbar_wait(bar + 8 * B_GO, 1);
        next = clock32();
      }
      if (i == 3) bar_sync<NB_LM, 128>();
      if (i == 4) next += DOWN_GAP;
      wait_until(next);
      next += FFN_GAP;
      if (elect_one())
        tma3(sb + OFF_FFN + 10240 * i, &P.wg + (i >> 1), bar + 8 * (i < 4 ? B_FFN : B_XS), i < 4 ? 32 * (b >> 1) : 0, i < 4 ? 0 : 16 * b, i < 4 ? 2 * rank + (i & 1) : 5 * (i & 1));
    }
  }
  TSTAMP(4);
}

__device__ __forceinline__ void run_helper(const Params& P, uint8_t* sm, uint32_t sb, int b, int hw, uint32_t ep, int budget, uint32_t poll_at) {
  const int h = threadIdx.x - 256, lane = h & 31, gq = lane >> 2, t = lane & 3, rank = b & 1, g = (b >> 1) & 7, j = b >> 4;
  const uint32_t bar = sb + OFF_BAR, prm = sb + OFF_PRM;
  uint4* const box = P.sc + b * BOX;
  const bool main20 = lane < 20;
  const int fin = 128 * (b >> 4) + 16 * ((b >> 2) & 3) + 2 * (b & 3) + (lane & 1) + 32 * (lane & 2) + 2 * (lane & 4);
  const int which = main20 ? 2 - hw : 3, fsl = (fin * 205) >> 14;
  const int q4 = main20 ? lane : min(10 * hw + lane - 20, 19);
  uint32_t wr[2];
  asm volatile("ld.global.nc.v2.u32 {%0, %1}, [%2];" : "=r"(wr[0]), "=r"(wr[1]) : "l"(P.wr + 80 * g + 4 * q4));
  uint32_t cw;
  asm volatile("ld.global.nc.u32 %0, [%1];" : "=r"(cw) : "l"(P.c + 160 * (b >> 5) + 2 * min(h, 79)));
  sts1(sb + OFF_SILU + 4 * min(h, 79), pack2(bf_lo(cw) * sigmoid(bf_lo(cw)), bf_hi(cw) * sigmoid(bf_hi(cw))));
  if (h < 4) sts1(prm + R_ONE + 4 * h, 0x3F803F80u);
  wait_until(poll_at);
  {
    uint32_t v[4][4];
    const int h80 = min(h, 79);
    const uint4* src = at<16>(P.sc + TABLES, 320 * j + h80);
#pragma unroll 1
    do {
#pragma unroll
      for (int i = 0; i < 4; ++i) ld_rlx4(v[i], src + i * 80);
    } while (retry<~0u>(stale<4, 2>(v, ep), budget));
#pragma unroll
    for (int i = 0; i < 4; ++i) sts2(sb + OFF_C1 + 16 * h80 + 1280 * (i & 1) + (i < 2 ? 8 : 0), v[i][0], v[i][1]);
    mbar_arrive(bar + 8 * B_TAB);
  }
  TSTAMP(3);
  bar_sync<NB_GO, 160>();
  {
    const char* src = hw == 2 ? at<128>(reinterpret_cast<const char*>(P.wdown), 160 * b + lane)
                              : at<128>(reinterpret_cast<const char*>(hw ? P.wup : P.wgate), (160 * (b & 3) + lane) * 27 + (b >> 2));
    uint4* slot = at<16>(box + M_HALO, h);
    uint32_t next = clock32() + TOUCH_AT + hw * (TOUCH_GAP / 3);
#pragma unroll 1
    for (int i = 0; i < 5; ++i) {
      wait_until(next);
      next += TOUCH_GAP;
      if (b < N_FFN) asm volatile("cp.async.cg.shared.global.L2::128B [%0], [%1], 16;" ::"r"(sb + OFF_SINK + 16 * h), "l"(src) : "memory");
      src += hw == 2 ? 4096 : 32 * 3456;
      if (i < 4) {
        st_rlx4(slot, ~ep, ~ep, ~ep, ~ep);
        st_rlx4(slot + 96, ~ep, ~ep, ~ep, ~ep);
      }
      slot += 192;
    }
  }
  bar_sync<NB_HELP, 128>();
  TSTAMP(5);

  {
    float d0[4] = {0.f, 0.f, 0.f, 0.f}, d1[4] = {0.f, 0.f, 0.f, 0.f};
    const uint32_t row = 8 * (lane >> 4) + (lane & 7), half = (lane >> 3) & 1, kstep = hw < 2 ? 2048 : 512;
    uint32_t wa = sb + OFF_LM + (hw < 2 ? row * 128 + (((4 * hw + half) ^ (lane & 7)) << 4) : 20480 + row * 32 + ((half ^ ((lane >> 2) & 1)) << 4)), sa = sb + OFF_SILU + (lane >> 3) * 16;
    mbar_wait(bar + 8 * B_XS, 1);
    {
      uint32_t hv[2][4] = {};
      const int q = min(2 * hw, 3);
      const uint4* const src = at<16>(box + (M_HALO - 16 * BOX), 32 * q + lane);
      mbar_wait(bar + 8 * B_EMPTY, 0);
      wait_until(clock32() + HALO_GAP);
      if (j > 0) gather<2, 32, 0>(hv, src, ep, budget);
      stsm4(sb + OFF_H + 512 * q + 16 * lane, hv[0]);
      stsm4(sb + OFF_H + 512 * q + 16 * lane + 512, hv[1]);
      bar_arrive<NB_HALO, 128>();
      if (j > 0) TSTAMP(4);
    }
    mbar_wait(bar + 8 * (B_EMPTY + 1), 0);
    TSTAMP(6);
    const uint32_t o1 = hw < 2 ? (wa ^ 32) - wa : 1024, s1 = hw < 2 ? 0 : 64;
#pragma unroll 1
    for (int u = hw < 2 ? 0 : 2; u < 5; ++u) {
      uint32_t a[4][4], s[2][4];
      ldsm4(s[0], sa);
      ldsm4t(a[0], wa);
      ldsm4t(a[1], wa + o1);
      ldsm4(s[1], sa + s1);
      ldsm4t(a[2], wa + kstep);
      ldsm4t(a[3], wa + kstep + o1);
      sched_fence(P.zero);
      mma16(d0, a[0], s[0][0], s[0][1], d0);
      if (hw < 2 || u < 4) mma16(d1, a[1], s[1][0], s[1][1], d1);
      mma16(d0, a[2], s[0][2], s[0][3], d0);
      if (hw < 2 || u < 4) mma16(d1, a[3], s[1][2], s[1][3], d1);
      wa += hw < 2 ? 4096 : 2048;
      sa += 64 + s1;
    }
    if (hw == 2) {
      d0[0] += d1[0];
      d0[2] += d1[2];
    }
    const float v = t & 2 ? (t & 1 ? d1[2] : d1[0]) : (t & 1 ? d0[2] : d0[0]);
    if (32 * hw + 8 * t < 80) st_rlx1(at<4>(box + M_LATE, 32 * hw + 8 * t + gq), tag(u32(v), ep));
  }
  if (b < N_FFN) {
    if (h == 0) mbar_expect_tx(bar + 8 * B_XS, 20480);
    bar_arrive<NB_LM, 128>();
  }
  TSTAMP(7);
  wait_until(clock32() + LATE_GAP);
  {
    uint32_t v[4][4];
    const int q = 160 * which + (main20 || hw < 2 ? 20 * g + q4 : min(fin >> 2, 159));
    const uint4* src = at<16>(P.sc + M_LATE, q < 512 ? (q >> 4) * BOX + (q & 15) : ((q - 512) >> 2) * BOX + 16 + (q & 3));
#pragma unroll 1
    do {
#pragma unroll
      for (int i = 0; i < 4; ++i) ld_rlx4(v[i], src + i * 32 * BOX);
    } while (retry<1>(stale<4, 0>(v, ep) | stale<4, 1>(v, ep) | stale<4, 2>(v, ep) | stale<4, 3>(v, ep), budget));
    const uint32_t one = which == 2 ? 0x3F803F80u : 0u;
    uint32_t w[2], pw[2];
#pragma unroll
    for (int e = 0; e < 2; ++e) {
      w[e] = fma2(pack2(f32(v[0][2 * e]) + f32(v[1][2 * e]) + f32(v[2][2 * e]) + f32(v[3][2 * e]),
                        f32(v[0][2 * e + 1]) + f32(v[1][2 * e + 1]) + f32(v[2][2 * e + 1]) + f32(v[3][2 * e + 1])), 0x3F803F80u, one);
      pw[e] = fma2(w[e], wr[e], 0x80008000u);
    }
    const uint32_t dst = prm + (main20 || hw < 2 ? 160 * which + 8 * q4 : R_FIN + 4 * (lane & 6));
    sts2(dst, w[0], w[1]);
    sts2(dst + 800, pw[0], pw[1]);
    float s = main20 ? bf_lo(pw[0]) + bf_hi(pw[0]) + bf_lo(pw[1]) + bf_hi(pw[1]) : 0.f;
#pragma unroll
    for (int o = 16; o > 0; o >>= 1) s += shx(s, o);
    sts1(sb + OFF_KEY + 64 + 4 * hw, u32(s));
    mbar_arrive(bar + 8 * B_TAB);
    mbar_wait(bar + 8 * B_TAB, 1);
  }
  TSTAMP(8);

  uint32_t ckey = 0;
  uint4* const odst = reinterpret_cast<uint4*>(P.out + (256 * j + rank) * 640 + 80 * g);
  if (hw == 0) {
    const uint32_t tile = min(4 * (lane & 3) + (lane >> 3), 9) * 16;
    uint32_t c1[4], sv[4], gb[4], x[4];
    ldsm4(c1, prm + R_C1 + tile);
    ldsm4(sv, prm + R_SB + tile);
    ldsm4(gb, prm + (lane & 4 ? R_GB + tile : R_ONE));
    const uint32_t bc = lds1(sb + OFF_KEY + 68), keep = lop3<0xF0>(gq & 4 ? ~0u : 0u, 0u, 0u);
    uint4* const cdst = at<16>(P.sc + M_CAND, (b - rank + (lane >> 4)) * BOX + 2 * (lane & 12) + 4 * rank + (lane & 3));
    uint32_t crow;
    {
      sched_fence(P.zero);
      bar_sync<NB_KEY, 288>();
      uint32_t k4[4];
      lds4(k4, sb + OFF_ROWS + 16 * lane);
      ckey = __reduce_max_sync(0xFFFFFFFFu, max(max(k4[0], k4[1]), max(k4[2], k4[3])));
      crow = (~ckey >> 1) & 127;
      TSTAMP(9);
      const uint32_t nw = lds1(sb + OFF_ROWS + 512 + 4 * crow);
      ldsm4(x, sb + OFF_X2 + crow * 176 + tile);
      const uint32_t rs = dup_hi(nw), nm = dup_lo(nw);
#pragma unroll
      for (int e = 0; e < 4; ++e) x[e] = fma2(gb[e], fma2(fma2(x[e], rs, nm), c1[e], sv[e]), x[e] & keep);
      st_rlx4(cdst, tag(x[0], ep), x[1], gq == 2 ? ckey : x[2], gq == 2 ? bc : x[3]);
    }
    bar_arrive<NB_PUB, 288>();
    TSTAMP(10);
    bar_sync<NB_OUT + 1, 160>();
    uint32_t next = clock32() + OUT_AT;
#pragma unroll 1
    for (int u = 0; u < 8; ++u) {
      if (u == 4) {
        bar_sync<NB_OUT, 160>();
        next = clock32();
      }
      wait_until(next);
      next += OUT_GAP;
      if (u != crow >> 4 && elect_one())
        asm volatile("cp.async.bulk.tensor.2d.global.shared::cta.bulk_group [%0, {%2, %3}], [%1];"
                     ::"l"(&P.om), "r"(sb + OFF_OUT + 2560 * u), "r"(640 * rank + 80 * g), "r"(128 * j + 16 * u) : "memory");
    }
    asm volatile("cp.async.bulk.commit_group;" ::: "memory");
    TSTAMP(11);
  } else {
    if (b >= 80 || hw == 2) return;
    bar_sync<NB_WIN, 64>();
  }
  uint32_t m[7][4], wkey = lds1(sb + OFF_KEY + 80);
  if (b >= N_FFN) {
    gather<1, 0, 0>(m, at<64>(P.sc + M_CAND + 16, (lane & 14) * (2 * BOX) + (lane & 1)), ep, budget);
    wkey = __reduce_max_sync(0xFFFFFFFFu, m[0][2]);
  }
  const uint32_t wtok = ~wkey & 2047;
  TSTAMP(12);
  if (hw == 0) {
    const uint32_t u = (~ckey >> 5) & 7, skip = ckey == wkey ? (~ckey >> 1) & 15 : 16;
#pragma unroll
    for (int i = 0; i < 5; ++i) {
      const uint32_t v = lane + 32 * i, r = (v * 205) >> 11;
      if (r != skip) *at<16>(odst, 2560 * u + v + 150 * r) = *reinterpret_cast<const uint4*>(sm + OFF_OUT + 2560 * u + 16 * v);
    }
    st_rlx1(at<4>(box + M_EPOCH, lane), ep);
    asm volatile("cp.async.bulk.wait_group.read 0;" ::: "memory");
    TSTAMP(15);
    TALIGN(1);
    return;
  } else {
    const int cn = fin - 80 * fsl;
    gather<1, 0, 0>(m, at<16>(P.sc + M_CAND, (16 * (wtok >> 8) + (lane & 8 ? 2 * (lane & 7) : 2 * fsl + 1)) * BOX + 4 * (wtok & 1) +
                                             (lane & 8 ? 16 : 8 * (cn >> 5) + ((cn >> 1) & 3))), ep, budget);
    const uint32_t bw = cn & 16 ? (cn & 8 ? m[0][3] : m[0][2]) : (cn & 8 ? m[0][1] : m[0][0]);
    const uint32_t gw = lds1(prm + R_FIN + 4 * (lane & 6) + 4 * (b & 1));
    float r = f32(m[0][3]);
#pragma unroll
    for (int o = 1; o < 8; o <<= 1) r += shx(r, o);
    r = __shfl_sync(0xFFFFFFFFu, r, 8) + f32(wkey >> 31 ? wkey & 0x7FFFF800u : ~wkey | 0x7FFu);
    const float sg = bf_round(sigmoid(bf_round(r))), gv = lane & 1 ? bf_hi(gw) : bf_lo(gw), bv = lane & 1 ? bf_hi(bw) : bf_lo(bw);
    __nv_bfloat16* const dst = at<2>(P.out, wtok * 640 + fin);
    const uint4* const src = at<16>(P.sc + M_YP, (4 * (lane >> 3) + ((b >> 2) & 3)) * BOX + 32 * j + 8 * (b & 3) + (lane & 7));
    TSTAMP(13);
    bar_sync<NB_YP, 64>();
    wait_until(clock32() + YP_GAP);
    gather_lazy<7, 16 * BOX, 32 * BOX, 0>(m, src, ep, budget, lane >= 24);
    TSTAMP(14);
    float y[4];
#pragma unroll
    for (int e = 0; e < 4; ++e)
      y[e] = ((f32(m[0][e]) + f32(m[1][e])) + (f32(m[2][e]) + f32(m[3][e]))) + ((f32(m[4][e]) + f32(m[5][e])) + f32(m[6][e]));
    const bool u1 = lane & 2, u2 = lane & 4;
    const float e0 = (u1 ? y[1] : y[0]) + shx(u1 ? y[0] : y[1], 2), e1 = (u1 ? y[3] : y[2]) + shx(u1 ? y[2] : y[3], 2);
    float e = (u2 ? e1 : e0) + shx(u2 ? e0 : e1, 4);
    e += shx(e, 8);
    e += shx(e, 16);
    asm volatile("{.reg .pred p; setp.lt.u32 p, %2, 8; @p st.global.b16 [%0], %1;}"
                 ::"l"(dst), "h"((uint16_t)pack2(fmaf(gv, bf_round(bf_round(e) * sg), bv), 0.f)), "r"(lane) : "memory");
  }
  TSTAMP(15);
}

template <int ODD> __device__ __forceinline__ uint32_t pack_acc(const float (&a)[96], const float (&b)[24], int part, int i, int h) {
  const int r = (i + 8 * ODD) % 10;
  const float* const v = r < 8 ? a + 32 * part + 4 * r : b + 8 * part + 4 * (r & 1);
  return pack2(v[2 * h], v[2 * h + 1]);
}
template <int V> struct Int { static constexpr int v = V; };
__device__ __forceinline__ constexpr int kpos(int i) { return i == 2 ? 8 : i == 7 ? 9 : i - (i > 2) - (i > 7); }

__device__ __forceinline__ void run_consumer(const Params& P, uint8_t* sm, uint32_t sb, int b, int warp, uint32_t ep, int budget) {
  const int tid = keep(threadIdx.x ^ 2), lane = tid & 31, gq = lane >> 2, t = lane & 3, p = warp >> 2, wq = warp & 3, rb = warp ^ 4;
  const int rank = b & 1, g = (b >> 1) & 7, j = b >> 4;
  const uint32_t bar = sb + OFF_BAR;
  uint4* const box = P.sc + b * BOX;
  const float z4[4] = {0.f, 0.f, 0.f, 0.f};

  uint32_t nrm[4];
  {
    uint32_t x[5][4], ones[10];
#pragma unroll
    for (int i = 0; i < 10; ++i) ones[i] = 0x3F803F80u;
    uint4* const dst = at<8>(box + M_ST1, tid >> 4);
    mbar_wait(bar + 8 * B_XS, 0);
    asm volatile("cp.async.wait_all;" ::: "memory");
    TSTAMP(4);
#pragma unroll
    for (int i = 0; i < 5; ++i) lds4(x[i], sb + OFF_XS + 4096 * i + 16 * tid);
    float s[4], qlo, qhi, mean, rstd;
    row_stats(s, qlo, qhi, x, ones, gq);
    const float q = __shfl_sync(0xFFFFFFFFu, qlo + qhi, 4 * gq + (gq >> 1));
    float v = t & 1 ? q : s[0] + s[2];
    v += shx(v, 4);
    v += shx(v, 8);
    const uint32_t nw = norm_word(v, shx(v, 1), mean, rstd);
    if ((lane & 15) == 0) st_rlx2(dst, nw, ep);
    TSTAMP(5);
    asm volatile("setmaxnreg.inc.sync.aligned.u32 224;");
  }

  float accA[96], accB[24];
#pragma unroll
  for (int i = 0; i < 96; ++i) asm volatile("" : "=f"(accA[i]));
#pragma unroll
  for (int i = 0; i < 24; ++i) asm volatile("" : "=f"(accB[i]));
  uint32_t xr[5][4];
#pragma unroll
  for (int i = 0; i < 20; ++i) asm volatile("" : "=r"(xr[i >> 2][i & 3]));
  const uint32_t turn = keep(NB_TURN + (tid >> 7)), pass = keep(NB_TURN + 1 - (tid >> 7));
  uint4* const opub = reinterpret_cast<uint4*>(__shfl_xor_sync(0xFFFFFFFFu, reinterpret_cast<uintptr_t>(at<16>(box + M_O, tid ^ 2)), 2));
  const uint4* src[7];
  const uint4* const lower = reinterpret_cast<const uint4*>(__shfl_xor_sync(0xFFFFFFFFu, reinterpret_cast<uintptr_t>(at<16>(P.sc + M_O, (b & ~14) * BOX + (tid ^ 2))), 2));
  const int l2 = lane ^ 2;
  const uint32_t ha = keep(sb + OFF_H + rb * 2560 + 16 * l2), lo = keep(sb + OFF_L + rb * 1280 + 16 * l2);
  const uint32_t va = keep(sb + OFF_H + 1280 + (rb + ((lane >> 3) & 1)) * 2560 + (lane >> 4) * 128 + (l2 & 7) * 16);
  const uint32_t M = keep((2 * (t ^ 2) > gq ? 0xFFFFu : 0u) | (2 * (t ^ 2) + 1 > gq ? 0xFFFF0000u : 0u)), gk = keep(g + (tid >> 9));
  {
    uint32_t la[4], raw[4][4], cw[4][4];
#pragma unroll
    for (int k = 0; k < 4; ++k) la[k] = keep(sb + (16 * rb + (l2 & 15)) * 128 + (((lane >> 4) ^ (l2 & 7) ^ (2 * k)) << 4));
    const uint32_t rel = keep(map_to_cta(bar + 8 * B_EMPTY, lane & 1)), c1a = keep(sb + OFF_C1 + 16 * (t ^ 2));
    const bool two = (ha & 0x1E0) == 0;
    constexpr uint64_t d0 = make_desc(SMEM_BASE + STAGE_A, 4096, 1024, 1), d1 = make_desc(SMEM_BASE + STAGE_A + STAGE_B0, 1024, 256, 3);
    const auto pick_x = [&](int st) {
#pragma unroll
      for (int k = 0; k < 4; ++k)
        if (g == (4 * st + k) / 5) ldsm4(xr[(4 * st + k) % 5], la[k] + (st & 3) * STAGE);
    };
    if (p == 1) turn_pass(pass);
    {
      const uint4* const src = at<8>(P.sc + M_ST1, (16 * j + 2 * rb) * 2 * BOX + 2 * gq + rank);
      mbar_wait(bar + 8 * B_FULL, 0);
#pragma unroll
      for (int k = 0; k < 4; ++k) ldsm4(raw[k], la[k]);
      pick_x(0);
      uint32_t n0[2], n1[2];
#pragma unroll 1
      do {
        ld_rlx2(n0, src);
        ld_rlx2(n1, src + BOX);
      } while (retry<~0u>(neq2(n0[1], n1[1], ep), budget));
      TSTAMP(6);
      mbar_wait(bar + 8 * B_TAB, 0);
      if (warp == 0) bar_arrive<NB_GO, 160>();
#pragma unroll
      for (int k = 0; k < 4; ++k) lds4(cw[k], c1a + 64 * k);
      nrm[0] = dup_hi(n0[0]); nrm[1] = dup_hi(n1[0]); nrm[2] = dup_lo(n0[0]); nrm[3] = dup_lo(n1[0]);
    }
    TSTAMP(7);
#pragma unroll
    for (int st = 0; st < 10; ++st) {
      uint32_t af[4][4];
#pragma unroll
      for (int k = 0; k < 16; ++k) raw[k >> 2][k & 3] = fma2(raw[k >> 2][k & 3], nrm[k & 1], nrm[2 + (k & 1)]);
      if (st) wg_wait();
      if (two) mbar_arrive_cluster(rel + 8 * ((st + 3) & 3));
#pragma unroll
      for (int k = 0; k < 16; ++k) af[k >> 2][k & 3] = fma2(raw[k >> 2][k & 3], cw[k >> 2][(k >> 1) & 1], cw[k >> 2][2 + ((k >> 1) & 1)]);
      if (st < 9) {
#pragma unroll
        for (int k = 0; k < 4; ++k) lds4(cw[k], c1a + 256 * (st + 1) + 64 * k);
      }
      wg_fence();
      turn_wait(turn);
#pragma unroll
      for (int k = 0; k < 4; ++k) {
        wgmma_n192(accA, af[k], d0 + ((st & 3) * STAGE + (k >> 1) * (STAGE_B0 / 2) + (k & 1) * 2048 >> 4), k + st);
        if (PASS1 == 2 * k) turn_pass(pass);
        wgmma_n48(accB, af[k], d1 + ((st & 3) * STAGE + (k >> 1) * (STAGE_B1 / 2) + (k & 1) * 512 >> 4), k + st);
        if (PASS1 == 2 * k + 1) turn_pass(pass);
      }
      wg_commit();
      if (st < 9) {
        mbar_wait(bar + 8 * ((st + 1) & 3), ((st + 1) >> 2) & 1);
#pragma unroll
        for (int k = 0; k < 4; ++k) ldsm4(raw[k], la[k] + ((st + 1) & 3) * STAGE);
        pick_x(st + 1);
      }
    }
    wg_wait();
    if (two) mbar_arrive_cluster(rel + 8);
  }
  TSTAMP(8);

  uint32_t o[5][4];
  {
    uint32_t hi[20], vl[10], kl[10], kh[10], vv[20], qf[4][4], qs[4][2];
    const auto pack_hi = [&](auto odd) {
#pragma unroll
      for (int i = 0; i < 10; ++i) {
        hi[kpos(i)] = pack_acc<odd.v>(accA, accB, 1, i, 1);
        hi[10 + i] = pack_acc<odd.v>(accA, accB, 2, i, 1);
      }
    };
    const auto pack_rest = [&](auto odd) {
#pragma unroll
      for (int i = 0; i < 10; ++i) {
        kl[kpos(i)] = pack_acc<odd.v>(accA, accB, 1, i, 0);
        vl[i] = pack_acc<odd.v>(accA, accB, 2, i, 0);
      }
#pragma unroll
      for (int i = 0; i < 16; ++i) qf[i >> 2][i & 3] = pack_acc<odd.v>(accA, accB, 0, 5 * (i >> 3) + 3 * ((i >> 2) & 1) + ((i >> 1) & 1), i & 1);
#pragma unroll
      for (int i = 0; i < 4; ++i) qs[i | 1][i & 1] = pack_acc<odd.v>(accA, accB, 0, 5 * (i >> 1) + 2, i & 1);
    };
    const auto stage = [&]() {
#pragma unroll
      for (int q = 0; q < 5; ++q) stsm4(ha + 2560 + 512 * q, hi + 4 * q);
      stsm4(lo, vl);
      stsm4(lo + 512, vl + 4);
      stsm2(lo + 1024, vl + 8);
    };
    const auto pack_all = [&](auto odd) {
      pack_hi(odd);
#pragma unroll
      for (int q = 0; q < 5; ++q) hi[4 * q] = tag(hi[4 * q], ep);
      if (rb == 7) {
#pragma unroll
        for (int q = 0; q < 5; ++q) st_rlx4(opub + (M_HALO - M_O - 96 + 32 * q), hi + 4 * q);
      }
      sched_fence(P.zero);
      TSTAMP(29);
      pack_rest(odd);
      stage();
    };
    if (g & 1) pack_all(Int<1>());
    else pack_all(Int<0>());
#pragma unroll
    for (int i = 0; i < 8; ++i) qs[i >> 1][i & 1] = (t >> 1) == ((i >> 1) & 1) ? qs[(i >> 1) | 1][i & 1] : 0u;
    __syncwarp();
    if (lane == 0) mbar_arrive(bar + 8 * B_HALO);
    float S0[4][4], S1[4][4], S2[4][4];
    ldsm4t(vl, lo);
    ldsm4t(vl + 4, lo + 512);
    ldsm2t(vl + 8, lo + 1024);
    sched_fence(P.zero);
#pragma unroll
    for (int hd = 0; hd < 4; ++hd) {
      mma16(S1[hd], qf[hd], kl[2 * hd], kl[2 * hd + 1], z4);
      mma16(S2[hd], qf[hd], hi[2 * hd], hi[2 * hd + 1], z4);
    }
#pragma unroll
    for (int hd = 0; hd < 4; ++hd) {
      mma8(S1[hd], qs[hd][0], qs[hd][1], kl[8 + (hd >> 1)], S1[hd]);
      mma8(S2[hd], qs[hd][0], qs[hd][1], hi[8 + (hd >> 1)], S2[hd]);
    }
    const bool up0 = M == ~0u, up1 = M != 0;
    uint32_t pp[4][2];
    const auto softmax = [&](const float (&A)[4][4], const float (&B)[4][4], int e) {
      const float SC = 0.22360679774997896f * 1.4426950408889634f;
      float a[4][2], mx[4];
#pragma unroll
      for (int hd = 0; hd < 4; ++hd) {
        a[hd][0] = up0 ? A[hd][2 * e] : B[hd][2 * e];
        a[hd][1] = up1 ? A[hd][2 * e + 1] : B[hd][2 * e + 1];
        mx[hd] = fmaxf(a[hd][0], a[hd][1]);
      }
#pragma unroll
      for (int s = 1; s < 4; s <<= 1) {
#pragma unroll
        for (int hd = 0; hd < 4; ++hd) mx[hd] = fmaxf(mx[hd], shx(mx[hd], s));
      }
#pragma unroll
      for (int hd = 0; hd < 4; ++hd) {
        const float ms = mx[hd] * -SC;
        pp[hd][e] = pack2(ex2(fmaf(a[hd][0], SC, ms)), ex2(fmaf(a[hd][1], SC, ms)));
      }
    };
#pragma unroll
    for (int i = 0; i < 7; ++i)
      asm volatile("{.reg .pred p; setp.gt.u32 p, %1, %2; selp.b64 %0, %3, %4, p;}" : "=l"(src[i]) : "r"(gk), "r"(i), "l"(lower), "l"(lower + 2 * BOX));
    TSTAMP(9);
    mbar_wait(bar + 8 * B_HALO, 0);
    if (rb == 0) bar_sync<NB_HALO, 128>();
    TSTAMP(10);
    ldsm4(kh, ha);
    ldsm4(kh + 4, ha + 512);
    ldsm2(kh + 8, ha + 1024);
#pragma unroll
    for (int i = 0; i < 5; ++i) ldsm4t(vv + 4 * i, va + 256 * i);
    const float ev = (j | rb) == 0 ? -1e9f / 0.22360679774997896f : 0.f, e4[4] = {ev, ev, ev, ev};
#pragma unroll
    for (int hd = 0; hd < 4; ++hd) mma16(S0[hd], qf[hd], kh[2 * hd], kh[2 * hd + 1], e4);
#pragma unroll
    for (int hd = 0; hd < 4; ++hd) mma8(S0[hd], qs[hd][0], qs[hd][1], kh[8 + (hd >> 1)], S0[hd]);
    softmax(S1, S2, 1);
    softmax(S0, S1, 0);
    float L[4][4], O[4][3][4];
#pragma unroll
    for (int hd = 0; hd < 4; ++hd) mma8(L[hd], pp[hd][0], pp[hd][1], 0x3F803F80u, z4);
#pragma unroll
    for (int hd = 0; hd < 4; ++hd) {
      const uint32_t p0 = pp[hd][0] & M, p2 = pp[hd][0] & ~M, p3 = pp[hd][1] & M, p5 = pp[hd][1] & ~M;
      const uint32_t z0 = pp[hd][0] & P.zero, z1 = pp[hd][1] & P.zero;
#pragma unroll
      for (int e = 0; e < 3; ++e) {
        const int f = 5 * (hd >> 1) + 2 * (hd & 1) + e;
        mma16(O[hd][e], p0, z0, z1, p5, vv[2 * f], vv[2 * f + 1], z4);
      }
#pragma unroll
      for (int e = 0; e < 3; ++e) mma8(O[hd][e], p2, p3, vl[5 * (hd >> 1) + 2 * (hd & 1) + e], O[hd][e]);
    }
    const bool odd = t >> 1;
#pragma unroll
    for (int hp = 0; hp < 2; ++hp) {
      const float (&A)[3][4] = O[2 * hp];
      const float (&B)[3][4] = O[2 * hp + 1];
#pragma unroll
      for (int e = 0; e < 2; ++e) {
        const float ra = rcp(L[2 * hp][2 * e]), rc = rcp(L[2 * hp + 1][2 * e]), rm = odd ? rc : ra;
        uint32_t* const d = &o[0][0] + 10 * hp + e;
        d[0] = pack2(A[0][2 * e] * ra, A[0][2 * e + 1] * ra);
        d[2] = pack2(A[1][2 * e] * ra, A[1][2 * e + 1] * ra);
        d[4] = pack2((odd ? B[0][2 * e] : A[2][2 * e]) * rm, (odd ? B[0][2 * e + 1] : A[2][2 * e + 1]) * rm);
        d[6] = pack2(B[1][2 * e] * rc, B[1][2 * e + 1] * rc);
        d[8] = pack2(B[2][2 * e] * rc, B[2][2 * e + 1] * rc);
      }
      if (hp == 0) {
#pragma unroll
        for (int s = 0; s < 2; ++s) {
          o[s][0] = tag(o[s][0], ep);
          st_rlx4(opub + 256 * s, o[s]);
        }
        sched_fence(P.zero);
        if (p == 1) bar_arrive<NB_PV, 256>();
      }
    }
#pragma unroll
    for (int s = 2; s < 5; ++s) o[s][0] = tag(o[s][0], ep);
  }
  TSTAMP(11);

  float acc[40];
#pragma unroll
  for (int i = 0; i < 40; ++i) asm volatile("" : "=f"(acc[i]));
  uint32_t ga[10], pb[10], uw;
  uint4* const sdst = at<16>(box + M_ST2, 16 * rb + gq);
  const uint32_t prow = sb + OFF_PRM + (lane >> 3) * 16;
  {
    const uint64_t dw = make_desc(sb, 5120, 512, 2);
    uint32_t in[5][7][4];
    const auto fetch = [&](int s) {
#pragma unroll
      for (int i = 0; i < 7; ++i) ld_rlx4(in[s][i], src[i] + (2 * BOX * i + 256 * s));
    };
    st_rlx4(opub + 256 * 2, o[2]);
    mbar_wait(bar + 8 * B_WO0, 0);
    if (p == 0) bar_sync<NB_PV, 256>();
    fetch(0);
    wg_fence();
    turn_wait(turn);
#pragma unroll
    for (int s = 0; s < 5; ++s) {
      wgmma_n80(acc, o[s], dw + (wo_off(0) + 1024 * s >> 4), s);
      if (s == PASS0) turn_pass(pass);
    }
    wg_commit();
    TSTAMP(12);
    mbar_wait(bar + 8 * B_WO1, 0);
    sched_fence(P.zero);
#pragma unroll 1
    while (retry<1>(stale<7, 0>(in[0], ep), budget)) {
#pragma unroll
      for (int i = 0; i < 7; ++i) ld_rlx4_stale(in[0][i], src[i] + 2 * BOX * i, in[0][i][0], ep);
    }
    TSTAMP(13);
    fetch(1);
    st_rlx4(opub + 256 * 3, o[3]);
    st_rlx4(opub + 256 * 4, o[4]);
#pragma unroll
    for (int s = 0; s < 5; ++s) {
      if (s == FGO_STEP && tid == 128) mbar_arrive(bar + 8 * B_GO);
      wg_fence();
      turn_wait(turn);
#pragma unroll
      for (int i = 0; i < 7; ++i) {
        wgmma_n80(acc, in[s][i], dw + (wo_off(i + 1) + 1024 * s >> 4), 1);
        if (i == PASS_AT - 1) {
          if (s < 4 || p == 0) turn_pass(pass);
          if (s == 4) {
            wg_commit();
            wg_fence();
          }
          if (s + AHEAD > 1 && s + AHEAD < 5) {
            wg_commit();
            asm volatile("wgmma.wait_group.sync.aligned %0;" ::"n"(AHEAD == 1 ? 3 : 1) : "memory");
            fetch(s + AHEAD);
            wg_fence();
          }
        }
      }
      wg_commit();
    }
    sched_fence(P.zero);
    asm volatile("wgmma.wait_group.sync.aligned 2;" ::: "memory");
    mbar_wait(bar + 8 * B_TAB, 1);
    ld_row(ga, prow + R_GA);
    ldsm4(pb, lane & 1 ? prow + R_P : sb + OFF_PRM + R_ONE);
    ldsm4(pb + 4, lane & 1 ? prow + R_P + 64 : sb + OFF_PRM + R_ONE);
    ldsm2(pb + 8, lane & 1 ? prow + R_P + 128 : sb + OFF_PRM + R_ONE);
    uw = tag(lds1(sb + OFF_KEY + 64), ep);
    const uint32_t bad = stale<28, 0>(in[1], ep) | FORCE_REDO;
    uint32_t redo;
    asm volatile("{.reg .pred p; setp.ne.u32 p, %1, 0; barrier.cta.red.or.aligned.pred p, %2, 128, p; selp.u32 %0, 1, 0, p;}"
                 : "=r"(redo) : "r"(bad & 1u), "r"(turn + (NB_REDO - NB_TURN)) : "memory");
    if (redo) {
      TSTAMP(17);
#pragma unroll 1
      for (int q = 0; q < 40; ++q) {
        const int i = q & 7, s = q >> 3;
        uint32_t a[1][4];
        wg_wait();
        gather<1, 0, 0>(a, lower + (2 * BOX * (i ? i - (i <= g) : g) + 256 * s), ep, budget);
        wg_fence();
        wgmma_n80(acc, a[0], dw + ((i < 4 ? 8 + i : i - 4) * WO + 1024 * s >> 4), q);
        wg_commit();
      }
    }
    wg_wait();
  }
  TSTAMP(18);

  uint32_t c1[10], sv[10], gb[10], nw;
  const uint32_t trow = 16 * rb + (lane & 15), xt = sb + (lane >> 4) * 16;
  {
#pragma unroll
    for (int k = 0; k < 20; ++k) acc2(xr[k >> 2][k & 3], ga[k >> 1], pack2(acc[2 * k], acc[2 * k + 1]));
    float s[4], qlo, qhi;
    row_stats(s, qlo, qhi, xr, pb, gq);
    if (t == gq >> 1) {
      st_rlx4(sdst, u32(s[0]), u32(s[1]), u32(qlo), uw);
      st_rlx4(sdst + 8, u32(s[2]), u32(s[3]), u32(qhi), uw);
    }
    sched_fence(P.zero);
    TSTAMP(19);
    const uint32_t tok = keep(256 * j + 32 * rb + (l2 & 30) + rank), kdst = keep(sb + OFF_ROWS + 64 * rb + 2 * (l2 & 30) + 512 * (lane & 1));
#pragma unroll
    for (int s5 = 0; s5 < 5; ++s5) stsm4(xt + trow * 176 + (OFF_X2 + 32 * s5), xr[s5]);
    uint32_t m[4][4];
    ld_row(c1, prow + R_C1);
    ld_row(sv, prow + R_SB);
    ld_row(gb, prow + R_GB);
    gather_lazy<4, 2 * BOX, 4 * BOX, 3>(m, at<16>(P.sc + M_ST2, (16 * j + rank + 8 * (lane & 1)) * BOX + 16 * rb + (lane >> 1)), ep, budget);
    TSTAMP(20);
#pragma unroll
    for (int e = 0; e < 4; ++e) {
      s[e] = (f32(m[0][e]) + f32(m[1][e])) + (f32(m[2][e]) + f32(m[3][e]));
      s[e] += shx(s[e], 1);
    }
    float mean, rstd;
    nw = norm_word(s[0], s[2], mean, rstd);
    const uint32_t u = u32(rstd * fmaf(-mean, s[3], s[1]));
    const uint32_t key = ((u ^ ((uint32_t)((int)u >> 31) | 0x80000000u)) | 2047u) ^ tok;
    sts1(kdst, lane & 1 ? nw : key);
    bar_arrive<NB_KEY, 288>();
    TSTAMP(21);
    bar_sync<NB_PUB, 288>();
  }
  TSTAMP(22);

  if (p == 0 && b < N_FFN) {
    uint32_t wf[20][4], m[6][4];
    mbar_wait(bar + 8 * B_FFN, 1);
#pragma unroll
    for (int i = 0; i < 20; ++i)
      ldsm4t(wf[i], sb + OFF_FFN + (lane & 8) * 2560 + (80 * wq + 8 * (lane >> 4) + (lane & 7)) * 64 + (((i & 3) ^ ((lane >> 1) & 3)) << 4) + 1024 * (i >> 2));
    TSTAMP(23);
    const uint32_t far = map_to_cta(sb, 0), dst = far + OFF_ACT + (4 * rank + wq) * 128 + gq * 16, step = map_to_cta(sb, 1) - far;
    gather_lazy<6, 64 * BOX, 8, 0>(m, at<16>(P.sc + M_CAND, (8 * (gq & 6) + 8 * rank + 2 * wq) * BOX + (lane & 7)), ep, budget);
    TSTAMP(24);
    const bool second = m[5][2] > m[4][2];
    const uint32_t wtok = ~__reduce_max_sync(0xFFFFFFFFu, max(m[4][2], m[5][2]));
    float f[4][4];
#pragma unroll
    for (int s = 0; s < 5; ++s) {
      const uint32_t b0 = second ? m[(s & 6) + 1][2 * (s & 1)] : m[s & 6][2 * (s & 1)], b1 = second ? m[(s & 6) + 1][2 * (s & 1) + 1] : m[s & 6][2 * (s & 1) + 1];
#pragma unroll
      for (int mt = 0; mt < 4; ++mt) mma16(f[mt], wf[4 * s + mt], b0, b1, s ? f[mt] : z4);
    }
    if (t == ((wtok >> 8) & 3)) {
      const bool e = wtok & 1;
#pragma unroll
      for (int r = 0; r < 2; ++r)
        asm volatile("st.async.weak.shared::cluster.mbarrier::complete_tx::bytes.v4.f32 [%0], {%1, %2, %3, %4}, [%5];"
                     ::"r"(dst + r * step), "f"(e ? f[2 * r][1] : f[2 * r][0]), "f"(e ? f[2 * r][3] : f[2 * r][2]),
                       "f"(e ? f[2 * r + 1][1] : f[2 * r + 1][0]), "f"(e ? f[2 * r + 1][3] : f[2 * r + 1][2]), "r"(far + r * step + (OFF_BAR + 8 * B_ACT)) : "memory");
    }
    __syncwarp();
    if (warp == 0) {
      sts1(sb + OFF_KEY + 80, ~wtok);
      if (b < 80) bar_arrive<NB_WIN, 64>();
    }
    TSTAMP(25);
  }
  {
    const uint32_t n0 = __shfl_sync(0xFFFFFFFFu, nw, 2 * gq), n1 = __shfl_sync(0xFFFFFFFFu, nw, 2 * gq + 16);
    nrm[0] = dup_hi(n0); nrm[1] = dup_hi(n1); nrm[2] = dup_lo(n0); nrm[3] = dup_lo(n1);
#pragma unroll
    for (int k = 0; k < 20; ++k) {
      uint32_t& x = xr[k >> 2][k & 3];
      acc2(x, gb[k >> 1], fma2(fma2(x, nrm[k & 1], nrm[2 + (k & 1)]), c1[k >> 1], sv[k >> 1]));
    }
  }
#pragma unroll
  for (int s5 = 0; s5 < 5; ++s5) stsm4(xt + trow * 160 + (OFF_OUT + 32 * s5), xr[s5]);
  asm volatile("fence.proxy.async.shared::cta;" ::: "memory");
  asm volatile("bar.arrive %0, 160;" ::"r"(turn + (NB_OUT - NB_TURN)) : "memory");
  if (p == 1 && b < N_FFN) {
    const uint32_t kr = ((lane & 7) >> 1) + 4 * (lane >> 4) + 8 * (lane & 1);
    uint32_t wd[10][4];
    mbar_wait(bar + 8 * B_XS, 0);
#pragma unroll
    for (int i = 0; i < 10; ++i) ldsm4t(wd[i], sb + OFF_FFN + 40960 + kr * 128 + (((2 * wq + ((lane >> 3) & 1)) ^ (kr & 7)) << 4) + 2048 * i);
    TSTAMP(23);
    uint4* const ydst = at<16>(P.sc + M_YP, ((b & ~3) + wq) * BOX + 4 * (gq & 6) + 2 * (b & 3) + (gq & 1));
    mbar_wait(bar + 8 * B_ACT, 1);
    TSTAMP(24);
    float v[8];
#pragma unroll
    for (int i = 0; i < 8; ++i) v[i] = f32(lds1(sb + OFF_ACT + 128 * i + 4 * lane));
    const float gu = bf_round(((v[0] + v[1]) + (v[2] + v[3])) + ((v[4] + v[5]) + (v[6] + v[7])));
    const float a = bf_round(gu * sigmoid(gu)) * shx(gu, 1);
    const uint32_t aw = pack2(a, shx(a, 2));
    const uint32_t b0 = __shfl_sync(0xFFFFFFFFu, aw, 4 * t), b1 = __shfl_sync(0xFFFFFFFFu, aw, 4 * t + 16);
    const bool odd = gq & 1;
    float y[5][4];
#pragma unroll
    for (int q = 0; q < 5; ++q) mma16(y[q], wd[2 * q], odd ? 0u : b0, odd ? 0u : b1, z4);
#pragma unroll
    for (int q = 0; q < 5; ++q) mma16(y[q], wd[2 * q + 1], odd ? b0 : 0u, odd ? b1 : 0u, y[q]);
    uint32_t w[4];
#pragma unroll
    for (int e = 0; e < 4; ++e) w[e] = u32(t & 2 ? (t & 1 ? y[3][e] : y[2][e]) : (t & 1 ? y[1][e] : y[0][e]));
    st_rlx4(ydst + 32 * t, tag(w[0], ep), w[1], w[2], w[3]);
    if (t == 0) st_rlx4(ydst + 128, tag(u32(y[4][0]), ep), u32(y[4][1]), u32(y[4][2]), u32(y[4][3]));
    __syncwarp();
    if (warp == 4 && b < 80) bar_arrive<NB_YP, 64>();
    TSTAMP(25);
  }
}

template <bool BY_SM>
__global__ void __cluster_dims__(2, 1, 1) __launch_bounds__(384, 1) fused_block_kernel(const __grid_constant__ Params P) {
  extern __shared__ __align__(1024) uint8_t sm[];
  const uint32_t sb = (uint32_t)__cvta_generic_to_shared(sm), t0 = clock32();
  const int tid = threadIdx.x, lane = tid & 31;
  uint32_t key = blockIdx.x;
  if (BY_SM) asm("mov.u32 %0, %%smid;" : "=r"(key));
  const __nv_bfloat16* wmod = (&P.wmod)[tid >> 9];
  asm volatile("" : "+l"(wmod));
  const int warp = __shfl_sync(0xFFFFFFFFu, tid >> 5, 0), c = key >> 1, rank = blockIdx.x & 1;
  const uint32_t bar = sb + OFF_BAR;
  const auto role = [&]() {
    const int q7 = ((c - (BY_SM ? 32 : 36)) * 37) >> 8;
    if (BY_SM) return 2 * pick(c < 32, 8 * (c & 7) + (c >> 3), pick(c < 60, 8 * c - 55 * q7 - 244, c - 58)) + rank;
    return 2 * pick(c < 4, c, pick(c < 36, 4 + 4 * ((c - 4) & 7) + ((c - 4) >> 3), 4 * c - 27 * q7 - 108)) + rank;
  };
  const bool spare = BY_SM && (c >> 1) == 30;
  int budget = SPIN_LIMIT, b;
  uint32_t e0 = 0;
  if (warp == 11) {
    if (elect_one()) {
#pragma unroll
      for (int i = 0; i < 12; ++i) mbar_init(bar + 8 * i, i == B_TAB ? 96 : i == B_HALO ? 8 : (i >> 2) == 1 ? 16 : 1);
      asm volatile("fence.mbarrier_init.release.cluster;" ::: "memory");
    }
    __syncwarp();
    asm volatile("barrier.cluster.arrive.relaxed.aligned;" ::: "memory");
    b = role();
    if (spare) {
      wait_until(t0 + 4000);
      return;
    }
    TSTAMP(27);
    const int g = (b >> 1) & 7;
    if (elect_one()) {
      mbar_expect_tx(bar + 8 * B_FULL, STAGE);
      tma2(sb, &P.xa, bar + 8 * B_FULL, 640 * rank, 128 * (b >> 4));
    }
    asm volatile("barrier.cluster.wait.aligned;" ::: "memory");
    if (elect_one()) {
      tma3_both(sb + STAGE_A + rank * (STAGE_B0 / 2), &P.w0, bar + 8 * B_FULL, 80 * g + 16 * (g & 1), 32 * rank, 0);
      tma3_both(sb + STAGE_A + STAGE_B0 + rank * (STAGE_B1 / 2), &P.w1, bar + 8 * B_FULL, 80 * g + 64 * (~g & 1), 32 * rank, 0);
    }
    TSTAMP(28);
    st_rlx1(at<4>(P.sc + M_ST1, b * (4 * BOX) + lane), 0u);
    __syncwarp();
    if (lane == 0) mbar_arrive(bar + 8 * B_XS);
  } else {
    asm volatile("barrier.cluster.arrive.relaxed.aligned;" ::: "memory");
    const int u = (c & 48) + 2 * (c & 7) + ((c >> 3) & 1) - (c & 32 ? c & 7 : 0), kb = 2 * u + rank;
    const bool gemv = warp < 10 && c < 40;
    uint32_t cv = 0;
    if (gemv) {
      const __nv_bfloat16* src = at<16>(wmod, (320 * rank + (tid >> 2)) * 480 + 4 * u + (tid & 3));
      const uint32_t dst = sb + 3 * STAGE + 16 * (tid ^ ((tid >> 3) & 3));
#pragma unroll
      for (int i = 0; i < 4; ++i)
        asm volatile("cp.async.cg.shared.global.L2::128B [%0], [%1], 16;" ::"r"(dst + 5120 * i), "l"(src + i * 80 * 3840) : "memory");
    } else if (warp == 10 && elect_one()) {
      asm volatile("prefetch.tensormap [%0];" ::"l"(&P.xa) : "memory");
      asm volatile("prefetch.tensormap [%0];" ::"l"(&P.w0) : "memory");
      asm volatile("prefetch.tensormap [%0];" ::"l"(&P.w1) : "memory");
    }
    TSTAMP(26);
    asm volatile("barrier.cluster.wait.aligned;" ::: "memory");
    if (spare) return;
    if (gemv) asm volatile("ld.global.nc.u16 %0, [%1];" : "=r"(cv) : "l"(at<2>(P.c, 320 * rank + 10 * (tid & 24) + ((tid >> 2) & ~7) + (tid & 7))));
    b = role();
    uint4* const box = P.sc + b * BOX;
    e0 = ld_rlx1(at<4>(box + M_EPOCH, lane));
    asm volatile("cp.async.commit_group;" ::: "memory");
    if (warp < 8) {
      const __nv_bfloat16* src = at<16>(P.x, (16 * b + (tid >> 4)) * 80 + (tid & 15));
      wait_until(t0 + XS_AT);
#pragma unroll
      for (int i = 0; i < 5; ++i)
        asm volatile("cp.async.cg.shared.global [%0], [%1], 16;" ::"r"(sb + OFF_XS + 4096 * i + 16 * tid), "l"(src + 128 * i) : "memory");
    }
    if (warp == 10) {
      uint4* const dst = at<16>(P.sc + TABLES, 80 * (lane & 28) + 4 * kb + (lane & 3));
      if (c < 40) st_rlx4(dst, 0u, 0u, 0u, 0u);
      if (lane == 0) mbar_expect_tx(bar + 8 * B_GO, c < 40 ? 1280 : 0);
      TALIGN(0);
      if (c < 40) {
        const uint32_t ep = next_epoch(e0);
        mbar_wait(bar + 8 * B_GO, 0);
        TSTAMP(1);
        float v[10];
#pragma unroll
        for (int i = 0; i < 10; ++i) v[i] = f32(lds1(sb + OFF_RED + 128 * i + 4 * lane));
        float s = ((v[0] + v[1]) + (v[2] + v[3])) + ((v[4] + v[5]) + (v[6] + v[7])) + (v[8] + v[9]);
        s += shx(s, 16);
        const uint32_t w = fma2(pack2(s, shx(s, 1)), 0x3F803F80u, kb < 40 ? 0u : 0x3F803F80u);
        st_rlx4(dst, __shfl_sync(0xFFFFFFFFu, w, 2 * (lane & 3)), __shfl_sync(0xFFFFFFFFu, w, 2 * (lane & 3) + 8), ep, ep);
        TSTAMP(2);
      }
    } else if (gemv) {
      const float x = bf_lo(cv), s = x * sigmoid(x);
      const uint32_t sw = pack2(s, shx(s, 1));
      uint32_t bw[4], a[4][4];
#pragma unroll
      for (int i = 0; i < 4; ++i) bw[i] = __shfl_sync(0xFFFFFFFFu, sw, 8 * i + 2 * (lane & 3));
      const uint32_t far = map_to_cta(sb, (lane >> 1) & 1), dst = far + OFF_RED + 128 * warp + 64 * rank + 32 * (lane & 1) + (lane & 28);
      const uint32_t la = sb + 3 * STAGE + 512 * warp + (lane >> 4) * 5120 + (lane & 7) * 64 + ((((lane >> 3) & 1) ^ ((lane >> 1) & 3)) << 4);
      sched_fence(P.zero);
      asm volatile("cp.async.wait_group 0;" ::: "memory");
      __syncwarp();
      TSTAMP(28);
#pragma unroll
      for (int i = 0; i < 4; ++i) ldsm4t(a[i], (la ^ (32 * (i & 1))) + (i >> 1) * 10240);
      float d[2][4];
      const float z4[4] = {0.f, 0.f, 0.f, 0.f};
#pragma unroll
      for (int i = 0; i < 4; ++i) mma16(d[i & 1], a[i], bw[i & 2], bw[(i & 2) + 1], i < 2 ? z4 : d[i & 1]);
      const float v = lane & 2 ? (lane & 1 ? d[1][2] : d[1][0]) : (lane & 1 ? d[0][2] : d[0][0]);
      asm volatile("st.async.weak.shared::cluster.mbarrier::complete_tx::bytes.f32 [%0], %1, [%2];" ::"r"(dst), "f"(v), "r"(far + OFF_BAR + 8 * B_GO) : "memory");
      TSTAMP(1);
    }
  }
  if (warp >= 8) {
    asm volatile("setmaxnreg.dec.sync.aligned.u32 56;");
    if (warp == 11) {
      wait_until(t0 + S_GAP);
      run_producer(P, sm, sb, b, t0);
    } else {
      run_helper(P, sm, sb, b, warp - 8, next_epoch(e0), budget, t0 + POLL_AT);
    }
    TDUMP();
  } else {
    run_consumer(P, sm, sb, b, warp, next_epoch(e0), budget);
    TDUMP();
  }
}

typedef CUresult (*EncodeFn)(CUtensorMap*, CUtensorMapDataType, cuuint32_t, void*, const cuuint64_t*, const cuuint64_t*, const cuuint32_t*,
                             const cuuint32_t*, CUtensorMapInterleave, CUtensorMapSwizzle, CUtensorMapL2promotion, CUtensorMapFloatOOBfill);

void encode(EncodeFn fn, CUtensorMap* m, const void* base, int rank, const cuuint64_t* dims, const cuuint64_t* strides, const cuuint32_t* box,
            CUtensorMapSwizzle sw) {
  const cuuint32_t es[3] = {1, 1, 1};
  fn(m, CU_TENSOR_MAP_DATA_TYPE_BFLOAT16, rank, const_cast<void*>(base), dims, strides, box, es, CU_TENSOR_MAP_INTERLEAVE_NONE, sw,
     CU_TENSOR_MAP_L2_PROMOTION_L2_128B, CU_TENSOR_MAP_FLOAT_OOB_FILL_NONE);
}

}

extern "C" void kernel_launch(void* const* d_in, const int* in_sizes, int n_in, void* d_out, int out_size) {
  (void)in_sizes; (void)n_in; (void)out_size;
  static EncodeFn fn = nullptr;
  static void* scratch = nullptr;
  static bool by_sm = false;
  if (!fn) {
    void* f = nullptr;
    cudaDriverEntryPointQueryResult q;
    cudaGetDriverEntryPoint("cuTensorMapEncodeTiled", &f, cudaEnableDefault, &q);
    fn = (EncodeFn)f;
    cudaFuncSetAttribute(fused_block_kernel<true>, cudaFuncAttributeMaxDynamicSharedMemorySize, SMEM_BYTES);
    cudaFuncSetAttribute(fused_block_kernel<false>, cudaFuncAttributeMaxDynamicSharedMemorySize, SMEM_BYTES);
    int dev = 0, sms = 0, pairs = 0;
    cudaGetDevice(&dev);
    cudaDeviceGetAttribute(&sms, cudaDevAttrMultiProcessorCount, dev);
    cudaLaunchConfig_t cfg = {};
    cudaLaunchAttribute at;
    at.id = cudaLaunchAttributeClusterDimension;
    at.val.clusterDim.x = 2;
    at.val.clusterDim.y = at.val.clusterDim.z = 1;
    cfg.gridDim = dim3(132);
    cfg.blockDim = dim3(384);
    cfg.dynamicSmemBytes = SMEM_BYTES;
    cfg.attrs = &at;
    cfg.numAttrs = 1;
    cudaOccupancyMaxActiveClusters(&pairs, fused_block_kernel<true>, &cfg);
    by_sm = sms == 132 && pairs == 66 && !NO_BY_SM;
    cudaGetSymbolAddress(&scratch, g_scratch);
  }
  Params P;
  P.sc = (uint4*)scratch;
  P.zero = 0;
  const cuuint64_t xd[2] = {1280, 1024}, xs[1] = {2560};
  const cuuint32_t xb[2] = {64, 128};
  encode(fn, &P.xa, d_in[0], 2, xd, xs, xb, CU_TENSOR_MAP_SWIZZLE_128B);
  const cuuint32_t ob[2] = {80, 16};
  encode(fn, &P.om, d_out, 2, xd, xs, ob, CU_TENSOR_MAP_SWIZZLE_NONE);
  const cuuint64_t wd3[3] = {640, 640, 3}, ws3[2] = {3840, 1280};
  const cuuint32_t w0b[3] = {64, 32, 3}, w1b[3] = {16, 32, 3};
  encode(fn, &P.w0, d_in[1], 3, wd3, ws3, w0b, CU_TENSOR_MAP_SWIZZLE_128B);
  encode(fn, &P.w1, d_in[1], 3, wd3, ws3, w1b, CU_TENSOR_MAP_SWIZZLE_32B);
  const cuuint64_t md[2] = {3840, 640}, ms[1] = {7680};
  const cuuint32_t mb0[2] = {64, 160}, mb1[2] = {16, 160};
  encode(fn, &P.wm0, d_in[9], 2, md, ms, mb0, CU_TENSOR_MAP_SWIZZLE_128B);
  encode(fn, &P.wm1, d_in[9], 2, md, ms, mb1, CU_TENSOR_MAP_SWIZZLE_32B);
  const cuuint64_t od3[3] = {608, 640, 2}, os3[2] = {1280, 64}, od2[2] = {640, 640}, os2[1] = {1280};
  const cuuint32_t oab[3] = {32, 80, 2}, obb[2] = {16, 80};
  encode(fn, &P.woa, d_in[2], 3, od3, os3, oab, CU_TENSOR_MAP_SWIZZLE_64B);
  encode(fn, &P.wob, d_in[2], 2, od2, os2, obb, CU_TENSOR_MAP_SWIZZLE_64B);
  const cuuint64_t gd[3] = {1728, 160, 4}, gs[2] = {3456, 160 * 3456}, dd[3] = {64, 1728, 10}, ds[2] = {1280, 128};
  const cuuint32_t gb[3] = {32, 160, 1}, db[3] = {64, 16, 5};
  encode(fn, &P.wg, d_in[5], 3, gd, gs, gb, CU_TENSOR_MAP_SWIZZLE_64B);
  encode(fn, &P.wu, d_in[6], 3, gd, gs, gb, CU_TENSOR_MAP_SWIZZLE_64B);
  encode(fn, &P.wd, d_in[7], 3, dd, ds, db, CU_TENSOR_MAP_SWIZZLE_128B);
  P.x = (const __nv_bfloat16*)d_in[0];
  P.wqkv = (const __nv_bfloat16*)d_in[1];
  P.wr = (const __nv_bfloat16*)d_in[4];
  P.wo = (const __nv_bfloat16*)d_in[2];
  P.wgate = (const __nv_bfloat16*)d_in[5];
  P.wup = (const __nv_bfloat16*)d_in[6];
  P.wdown = (const __nv_bfloat16*)d_in[7];
  P.c = (const __nv_bfloat16*)d_in[8];
  P.wmod = (const __nv_bfloat16*)d_in[9];
  P.out = (__nv_bfloat16*)d_out;
  if (by_sm) fused_block_kernel<true><<<132, 384, SMEM_BYTES>>>(P);
  else fused_block_kernel<false><<<128, 384, SMEM_BYTES>>>(P);
}
```

```cpp
#include <cuda_runtime.h>
#include <cuda.h>
#include <cuda_bf16.h>
#include <stdint.h>

namespace {

constexpr int STAGE_A = 16384, STAGE_B0 = 24576, STAGE_B1 = 6144, STAGE = STAGE_A + STAGE_B0 + STAGE_B1;
constexpr int WO = 15360;
constexpr int OFF_FFN = 4 * WO, OFF_LM = 2 * STAGE, OFF_X2 = 4 * STAGE, OFF_OUT = 0;
constexpr int OFF_H = 4 * STAGE, OFF_L = OFF_H + 9 * 2560, OFF_XS = OFF_H, OFF_RED = OFF_L, OFF_SINK = OFF_L + 10240;
constexpr int OFF_C1 = 225280, OFF_ACT = OFF_C1, OFF_ROWS = OFF_C1 + 1024, OFF_PRM = OFF_C1 + 2560, OFF_SILU = OFF_PRM + 1600;
constexpr int OFF_KEY = OFF_SILU + 320, OFF_BAR = OFF_KEY + 128, SMEM_BYTES = OFF_BAR + 256;
static_assert(OFF_H % 512 == 0, "lane bits of the halo address");
static_assert(SMEM_BYTES <= 232448 && OFF_BAR % 64 == 0, "smem");
enum { R_GA = 0, R_SB = 160, R_C1 = 320, R_GB = 480, R_FIN = 640, R_P = 800 + R_C1, R_ONE = 704 };

enum { B_FULL = 0, B_EMPTY = 4, B_HALO = 8, B_TAB = 9, B_GO = 10, B_XS = 11, B_ACT = B_FULL, B_FFN = B_FULL + 1, B_WO0 = B_FULL + 2, B_WO1 = B_FULL + 3 };
enum { NB_PV = 1, NB_TURN = 2, NB_KEY = 4, NB_REDO = 5, NB_HELP = 6, NB_HALO = 7, NB_PUB = 8, NB_GO = 9, NB_LM = 10, NB_OUT = 11, NB_WIN = 13, NB_YP = 14 };

enum { M_EARLY = 0, M_ST1 = 32, M_EPOCH = 40, M_HALO = 48, M_ST2 = 208, M_CAND = 336, M_LATE = 368, M_YP = 400, M_O = 560, BOX = 1840 };
constexpr int TABLES = 128 * BOX;
__device__ __align__(1024) uint4 g_scratch[TABLES + 8 * 320];

constexpr int N_FFN = 108;
constexpr uint32_t SMEM_BASE = 1024;
constexpr int AHEAD = 1;
constexpr int FFN_EARLY = 0;
constexpr int DOWN_GAP = 1900;
constexpr int NAP = 20;
constexpr int XS_AT = 900;
constexpr int S_GAP = 1300;
constexpr int POLL_AT = 4000;
constexpr int WPF_AT = 3500;
constexpr int LMPF_AT = 4;
constexpr int TOUCH_AT = 1000;
constexpr int TOUCH_GAP = 1100;
constexpr int HALO_GAP = 400;
constexpr int LATE_GAP = 800;
constexpr int FGO_STEP = 4;
constexpr int FFN_GAP = 0;
constexpr int OUT_AT = 400;
constexpr int OUT_GAP = 0;
constexpr int YP_GAP = 250;
constexpr int PASS1 = 5;
constexpr int PASS0 = 2;
constexpr int PASS_AT = 3;
constexpr int SPIN_LIMIT = 1 << 16;

struct Params {
  const __nv_bfloat16 *wmod, *c, *x;
  uint4* sc;
  uint32_t zero;
  const __nv_bfloat16 *wqkv, *wr, *wo, *wgate, *wup, *wdown;
  __nv_bfloat16* out;
  CUtensorMap xa, w0, w1, wm0, wm1, woa, wob, wg, wu, wd, om;
};

__device__ __forceinline__ uint32_t clock32() {
  uint32_t c;
  asm volatile("mov.u32 %0, %%clock;" : "=r"(c));
  return c;
}

__device__ __forceinline__ void mbar_init(uint32_t b, uint32_t c) { asm volatile("mbarrier.init.shared::cta.b64 [%0], %1;" ::"r"(b), "r"(c) : "memory"); }
__device__ __forceinline__ void mbar_expect_tx(uint32_t b, uint32_t n) { asm volatile("mbarrier.arrive.expect_tx.shared::cta.b64 _, [%0], %1;" ::"r"(b), "r"(n) : "memory"); }
__device__ __forceinline__ void mbar_arrive(uint32_t b) { asm volatile("mbarrier.arrive.shared::cta.b64 _, [%0];" ::"r"(b) : "memory"); }
__device__ __forceinline__ uint32_t map_to_cta(uint32_t a, uint32_t rank) {
  uint32_t r;
  asm("mapa.shared::cluster.u32 %0, %1, %2;" : "=r"(r) : "r"(a), "r"(rank));
  return r;
}
__device__ __forceinline__ void mbar_arrive_cluster(uint32_t b) { asm volatile("mbarrier.arrive.shared::cluster.b64 _, [%0];" ::"r"(b) : "memory"); }
__device__ __forceinline__ void mbar_wait(uint32_t b, uint32_t ph) {
  asm volatile("{.reg .pred p;\n"
               "RETRY: mbarrier.try_wait.parity.shared::cta.b64 p, [%0], %1;\n"
               "@!p bra RETRY;}" ::"r"(b), "r"(ph) : "memory");
}
__device__ __forceinline__ bool elect_one() {
  uint32_t r;
  asm volatile("{.reg .pred p; elect.sync _|p, 0xFFFFFFFF; selp.u32 %0, 1, 0, p;}" : "=r"(r));
  return r;
}
template <int ID, int N> __device__ __forceinline__ void bar_sync() { asm volatile("bar.sync %0, %1;" ::"n"(ID), "n"(N) : "memory"); }
template <int ID, int N> __device__ __forceinline__ void bar_arrive() { asm volatile("bar.arrive %0, %1;" ::"n"(ID), "n"(N) : "memory"); }
__device__ __forceinline__ void turn_wait(uint32_t id) { asm volatile("bar.sync %0, 256;" ::"r"(id) : "memory"); }
__device__ __forceinline__ void turn_pass(uint32_t id) { asm volatile("bar.arrive %0, 256;" ::"r"(id) : "memory"); }
__device__ __forceinline__ void tma2(uint32_t dst, const CUtensorMap* m, uint32_t bar, int c0, int c1) {
  asm volatile("cp.async.bulk.tensor.2d.shared::cluster.global.mbarrier::complete_tx::bytes [%0], [%1, {%3, %4}], [%2];" ::"r"(dst), "l"(m), "r"(bar), "r"(c0), "r"(c1) : "memory");
}
__device__ __forceinline__ void tma3(uint32_t dst, const CUtensorMap* m, uint32_t bar, int c0, int c1, int c2) {
  asm volatile("cp.async.bulk.tensor.3d.shared::cluster.global.mbarrier::complete_tx::bytes [%0], [%1, {%3, %4, %5}], [%2];" ::"r"(dst), "l"(m), "r"(bar), "r"(c0), "r"(c1), "r"(c2) : "memory");
}
__device__ __forceinline__ void tma2_both(uint32_t dst, const CUtensorMap* m, uint32_t bar, int c0, int c1) {
  asm volatile("cp.async.bulk.tensor.2d.shared::cluster.global.mbarrier::complete_tx::bytes.multicast::cluster [%0], [%1, {%3, %4}], [%2], %5;"
               ::"r"(dst), "l"(m), "r"(bar), "r"(c0), "r"(c1), "h"((uint16_t)3) : "memory");
}
__device__ __forceinline__ void tma3_both(uint32_t dst, const CUtensorMap* m, uint32_t bar, int c0, int c1, int c2) {
  asm volatile("cp.async.bulk.tensor.3d.shared::cluster.global.mbarrier::complete_tx::bytes.multicast::cluster [%0], [%1, {%3, %4, %5}], [%2], %6;"
               ::"r"(dst), "l"(m), "r"(bar), "r"(c0), "r"(c1), "r"(c2), "h"((uint16_t)3) : "memory");
}
__device__ __forceinline__ void bulk_prefetch(const void* src, uint32_t bytes) {
  asm volatile("cp.async.bulk.prefetch.L2.global [%0], %1;" ::"l"(src), "r"(bytes) : "memory");
}
__device__ __forceinline__ void wg_fence() { asm volatile("wgmma.fence.sync.aligned;" ::: "memory"); }
__device__ __forceinline__ void wg_commit() { asm volatile("wgmma.commit_group.sync.aligned;" ::: "memory"); }
__device__ __forceinline__ void wg_wait() { asm volatile("wgmma.wait_group.sync.aligned 0;" ::: "memory"); }
__device__ __forceinline__ constexpr uint64_t make_desc(uint32_t addr, uint32_t lbo, uint32_t sbo, uint32_t mode) {
  return (uint64_t)((addr & 0x3FFFF) >> 4) | ((uint64_t)(lbo >> 4) << 16) | ((uint64_t)(sbo >> 4) << 32) | ((uint64_t)mode << 62);
}
__device__ __forceinline__ void ldsm4(uint32_t& r0, uint32_t& r1, uint32_t& r2, uint32_t& r3, uint32_t a) {
  asm volatile("ldmatrix.sync.aligned.m8n8.x4.shared.b16 {%0, %1, %2, %3}, [%4];" : "=r"(r0), "=r"(r1), "=r"(r2), "=r"(r3) : "r"(a) : "memory");
}
__device__ __forceinline__ void ldsm4(uint32_t* r, uint32_t a) { ldsm4(r[0], r[1], r[2], r[3], a); }
__device__ __forceinline__ void ldsm2(uint32_t* r, uint32_t a) {
  asm volatile("ldmatrix.sync.aligned.m8n8.x2.shared.b16 {%0, %1}, [%2];" : "=r"(r[0]), "=r"(r[1]) : "r"(a) : "memory");
}
__device__ __forceinline__ void ldsm4t(uint32_t* r, uint32_t a) {
  asm volatile("ldmatrix.sync.aligned.m8n8.x4.trans.shared.b16 {%0, %1, %2, %3}, [%4];" : "=r"(r[0]), "=r"(r[1]), "=r"(r[2]), "=r"(r[3]) : "r"(a) : "memory");
}
__device__ __forceinline__ void ldsm2t(uint32_t* r, uint32_t a) {
  asm volatile("ldmatrix.sync.aligned.m8n8.x2.trans.shared.b16 {%0, %1}, [%2];" : "=r"(r[0]), "=r"(r[1]) : "r"(a) : "memory");
}
__device__ __forceinline__ void ld_row(uint32_t (&r)[10], uint32_t a) {
  ldsm4(r, a);
  ldsm4(r + 4, a + 64);
  ldsm2(r + 8, a + 128);
}
__device__ __forceinline__ void stsm4(uint32_t a, const uint32_t* r) {
  asm volatile("stmatrix.sync.aligned.m8n8.x4.shared.b16 [%0], {%1, %2, %3, %4};" ::"r"(a), "r"(r[0]), "r"(r[1]), "r"(r[2]), "r"(r[3]) : "memory");
}
__device__ __forceinline__ void stsm2(uint32_t a, const uint32_t* r) {
  asm volatile("stmatrix.sync.aligned.m8n8.x2.shared.b16 [%0], {%1, %2};" ::"r"(a), "r"(r[0]), "r"(r[1]) : "memory");
}
__device__ __forceinline__ void lds4(uint32_t* r, uint32_t a) {
  asm volatile("ld.shared.v4.u32 {%0, %1, %2, %3}, [%4];" : "=r"(r[0]), "=r"(r[1]), "=r"(r[2]), "=r"(r[3]) : "r"(a) : "memory");
}
__device__ __forceinline__ uint32_t lds1(uint32_t a) {
  uint32_t v;
  asm volatile("ld.shared.u32 %0, [%1];" : "=r"(v) : "r"(a) : "memory");
  return v;
}
__device__ __forceinline__ void sts1(uint32_t a, uint32_t v) { asm volatile("st.shared.u32 [%0], %1;" ::"r"(a), "r"(v) : "memory"); }
__device__ __forceinline__ void sts2(uint32_t a, uint32_t v0, uint32_t v1) { asm volatile("st.shared.v2.u32 [%0], {%1, %2};" ::"r"(a), "r"(v0), "r"(v1) : "memory"); }
__device__ __forceinline__ void mma16(float (&d)[4], uint32_t a0, uint32_t a1, uint32_t a2, uint32_t a3, uint32_t b0, uint32_t b1, const float* c) {
  asm volatile("mma.sync.aligned.m16n8k16.row.col.f32.bf16.bf16.f32 {%0, %1, %2, %3}, {%4, %5, %6, %7}, {%8, %9}, {%10, %11, %12, %13};"
               : "=f"(d[0]), "=f"(d[1]), "=f"(d[2]), "=f"(d[3])
               : "r"(a0), "r"(a1), "r"(a2), "r"(a3), "r"(b0), "r"(b1), "f"(c[0]), "f"(c[1]), "f"(c[2]), "f"(c[3]));
}
__device__ __forceinline__ void mma16(float (&d)[4], const uint32_t* a, uint32_t b0, uint32_t b1, const float* c) { mma16(d, a[0], a[1], a[2], a[3], b0, b1, c); }
__device__ __forceinline__ void mma8(float (&d)[4], uint32_t a0, uint32_t a1, uint32_t b0, const float* c) {
  asm volatile("mma.sync.aligned.m16n8k8.row.col.f32.bf16.bf16.f32 {%0, %1, %2, %3}, {%4, %5}, {%6}, {%7, %8, %9, %10};"
               : "=f"(d[0]), "=f"(d[1]), "=f"(d[2]), "=f"(d[3]) : "r"(a0), "r"(a1), "r"(b0), "f"(c[0]), "f"(c[1]), "f"(c[2]), "f"(c[3]));
}
__device__ __forceinline__ uint32_t pack2(float lo, float hi) {
  uint32_t r;
  asm volatile("cvt.rn.bf16x2.f32 %0, %1, %2;" : "=r"(r) : "f"(hi), "f"(lo));
  return r;
}
__device__ __forceinline__ float bf_lo(uint32_t w) { return __uint_as_float(w << 16); }
__device__ __forceinline__ float bf_hi(uint32_t w) { return __uint_as_float(w & 0xFFFF0000u); }
__device__ __forceinline__ float bf_round(float v) { return __uint_as_float(pack2(0.f, v)); }
__device__ __forceinline__ uint32_t fma2(uint32_t a, uint32_t b, uint32_t c) {
  uint32_t r;
  asm("fma.rn.bf16x2 %0, %1, %2, %3;" : "=r"(r) : "r"(a), "r"(b), "r"(c));
  return r;
}
__device__ __forceinline__ void acc2(uint32_t& c, uint32_t a, uint32_t b) { asm("fma.rn.bf16x2 %0, %1, %2, %0;" : "+r"(c) : "r"(a), "r"(b)); }
__device__ __forceinline__ float ex2(float v) {
  float r;
  asm("ex2.approx.ftz.f32 %0, %1;" : "=f"(r) : "f"(v));
  return r;
}
__device__ __forceinline__ float rcp(float v) {
  float r;
  asm("rcp.approx.ftz.f32 %0, %1;" : "=f"(r) : "f"(v));
  return r;
}
__device__ __forceinline__ float rsq(float v) {
  float r;
  asm("rsqrt.approx.ftz.f32 %0, %1;" : "=f"(r) : "f"(v));
  return r;
}
__device__ __forceinline__ float sigmoid(float v) { return rcp(1.f + ex2(v * -1.4426950408889634f)); }
__device__ __forceinline__ float f32(uint32_t v) { return __uint_as_float(v); }
__device__ __forceinline__ uint32_t u32(float v) { return __float_as_uint(v); }
__device__ __forceinline__ void ld_rlx4(uint32_t* v, const void* p) {
  asm volatile("{.reg .b128 q; ld.relaxed.gpu.global.b128 q, [%4]; mov.b128 {%0, %1, %2, %3}, q;}" : "=r"(v[0]), "=r"(v[1]), "=r"(v[2]), "=r"(v[3]) : "l"(p) : "memory");
}
__device__ __forceinline__ void ld_rlx2(uint32_t* v, const void* p) {
  asm volatile("{.reg .b64 q; ld.relaxed.gpu.global.b64 q, [%2]; mov.b64 {%0, %1}, q;}" : "=r"(v[0]), "=r"(v[1]) : "l"(p) : "memory");
}
__device__ __forceinline__ uint32_t ld_rlx1(const void* p) {
  uint32_t v;
  asm volatile("ld.relaxed.gpu.global.u32 %0, [%1];" : "=r"(v) : "l"(p) : "memory");
  return v;
}
__device__ __forceinline__ void st_rlx4(void* p, uint32_t a, uint32_t b, uint32_t c, uint32_t d) {
  asm volatile("{.reg .b128 q; mov.b128 q, {%1, %2, %3, %4}; st.relaxed.gpu.global.b128 [%0], q;}" ::"l"(p), "r"(a), "r"(b), "r"(c), "r"(d) : "memory");
}
__device__ __forceinline__ void st_rlx4(void* p, const uint32_t* v) { st_rlx4(p, v[0], v[1], v[2], v[3]); }
__device__ __forceinline__ void st_rlx2(void* p, uint32_t a, uint32_t b) { asm volatile("{.reg .b64 q; mov.b64 q, {%1, %2}; st.relaxed.gpu.global.b64 [%0], q;}" ::"l"(p), "r"(a), "r"(b) : "memory"); }
__device__ __forceinline__ void st_rlx1(void* p, uint32_t v) { asm volatile("st.relaxed.gpu.global.u32 [%0], %1;" ::"l"(p), "r"(v) : "memory"); }
template <int LUT> __device__ __forceinline__ uint32_t lop3(uint32_t a, uint32_t b, uint32_t c) {
  uint32_t r;
  asm volatile("lop3.b32 %0, %1, %2, %3, %4;" : "=r"(r) : "r"(a), "r"(b), "r"(c), "n"(LUT));
  return r;
}
__device__ __forceinline__ uint32_t tag(uint32_t w, uint32_t ep) { return lop3<0xD8>(w, ep, 1u); }
__device__ __forceinline__ uint32_t neq2(uint32_t a, uint32_t b, uint32_t e) { return lop3<0x7E>(a, b, e); }
__device__ __forceinline__ uint32_t next_epoch(uint32_t e) {
  asm volatile("add.u32 %0, %0, 1;" : "+r"(e));
  return e;
}
__device__ __forceinline__ void sched_fence(uint32_t zero) {
  asm volatile("{.reg .pred p; setp.ne.u32 p, %0, 0;\nSPIN: pmevent 0; @p bra.uni SPIN;}" ::"r"(zero) : "memory");
}
__device__ __forceinline__ int pick(bool c, int a, int b) {
  int r;
  asm("{.reg .pred p; setp.ne.u32 p, %1, 0; selp.b32 %0, %2, %3, p;}" : "=r"(r) : "r"((uint32_t)c), "r"(a), "r"(b));
  return r;
}
__device__ __forceinline__ uint32_t keep(uint32_t v) { return __shfl_xor_sync(0xFFFFFFFFu, v, 2); }
__device__ __forceinline__ void wait_until(uint32_t t) {
  while ((int)(clock32() - t) < 0) {
    asm volatile("nanosleep.u32 %0;" ::"n"(NAP));
  }
}
__device__ __forceinline__ float shx(float v, int o) { return __shfl_xor_sync(0xFFFFFFFFu, v, o); }
template <int SCALE, class T> __device__ __forceinline__ T* at(T* base, uint32_t i) {
  T* r;
  asm volatile("mad.wide.u32 %0, %1, %2, %3;" : "=l"(r) : "r"(i), "n"(SCALE), "l"(base));
  return r;
}
template <uint32_t MASK> __device__ __forceinline__ bool retry(uint32_t bad, int& budget) {
  uint32_t r;
  asm volatile("{.reg .pred p, q; .reg .b32 t; add.s32 %1, %1, -1; setp.gt.s32 q, %1, 0; and.b32 t, %2, %3; setp.ne.u32 p, t, 0;\n"
               "vote.sync.any.pred p, p, 0xFFFFFFFF; and.pred p, p, q; selp.u32 %0, 1, 0, p;}" : "=r"(r), "+r"(budget) : "r"(bad), "n"(MASK));
  return r;
}
template <int N, int W> __device__ __forceinline__ uint32_t stale(const uint32_t (*v)[4], uint32_t ep) {
  uint32_t bad = neq2(v[0][W], v[N > 1][W], ep);
#pragma unroll
  for (int i = 2; i < N; i += 2) bad |= neq2(v[i][W], v[i + 1 < N ? i + 1 : i][W], ep);
  return bad;
}
__device__ __forceinline__ void ld_rlx4_stale(uint32_t* v, const void* p, uint32_t w, uint32_t ep) {
  asm volatile("{.reg .b128 q; .reg .pred p; .reg .b32 t; lop3.b32 t, %5, %6, 1, 0x28; setp.ne.u32 p, t, 0; mov.b128 q, {%0, %1, %2, %3};\n"
               "@p ld.relaxed.gpu.global.b128 q, [%4]; mov.b128 {%0, %1, %2, %3}, q;}"
               : "+r"(v[0]), "+r"(v[1]), "+r"(v[2]), "+r"(v[3]) : "l"(p), "r"(w), "r"(ep) : "memory");
}
template <int N, int S0, int S1, int W> __device__ __forceinline__ void gather_lazy(uint32_t (*v)[4], const uint4* p, uint32_t ep, int& budget, bool skip_last = false) {
#pragma unroll
  for (int i = 0; i < 4 * N; ++i) {
    if ((i & 3) == W) v[i >> 2][W] = N == 7 && i >= 24 && skip_last ? ep & 1u : ~ep;
    else if (N == 7 && i >= 24) v[6][i & 3] = 0;
    else asm volatile("" : "=r"(v[i >> 2][i & 3]));
  }
#pragma unroll 1
  do {
#pragma unroll
    for (int i = 0; i < N; ++i) ld_rlx4_stale(v[i], p + (i & 1) * S0 + (i >> 1) * S1, v[i][W], ep);
  } while (retry<1>(stale<N, W>(v, ep), budget));
}
template <int N, int STRIDE, int W> __device__ __forceinline__ void gather(uint32_t (*v)[4], const uint4* p, uint32_t ep, int& budget) {
#pragma unroll 1
  do {
#pragma unroll
    for (int i = 0; i < N; ++i) ld_rlx4(v[i], p + i * STRIDE);
  } while (retry<1>(stale<N, W>(v, ep), budget));
}
__device__ __forceinline__ void row_stats(float (&s)[4], float& qlo, float& qhi, const uint32_t (&x)[5][4], const uint32_t (&b)[10], int gq) {
  const float z[4] = {0.f, 0.f, 0.f, 0.f};
  float q[4][4];
#pragma unroll
  for (int i = 0; i < 5; ++i) {
    mma16(s, x[i], b[2 * i], b[2 * i + 1], i ? s : z);
#pragma unroll
    for (int e = 0; e < 4; ++e) mma8(q[e], x[i][e & 2], x[i][(e & 2) + 1], x[i][e], i ? q[e] : z);
  }
  const bool odd = gq & 1;
  qlo = (odd ? q[0][1] : q[0][0]) + (odd ? q[2][1] : q[2][0]);
  qhi = (odd ? q[1][3] : q[1][2]) + (odd ? q[3][3] : q[3][2]);
}
__device__ __forceinline__ uint32_t norm_word(float s, float q, float& mean, float& rstd) {
  mean = s * (1.f / 640.f);
  rstd = rsq(fmaxf(fmaf(q, 1.f / 640.f, -mean * mean), 0.f) + 1e-5f);
  return pack2(-mean * bf_round(rstd), rstd);
}
__device__ __forceinline__ uint32_t dup_lo(uint32_t w) { return __byte_perm(w, 0u, 0x1010); }
__device__ __forceinline__ uint32_t dup_hi(uint32_t w) { return __byte_perm(w, 0u, 0x3232); }

__device__ __forceinline__ void wgmma_n192(float (&d)[96], const uint32_t (&a)[4], uint64_t db, int add) {
  asm volatile("{.reg .pred p; setp.ne.b32 p, %101, 0; wgmma.mma_async.sync.aligned.m64n192k16.f32.bf16.bf16 "
    "{%0, %1, %2, %3, %4, %5, %6, %7, %8, %9, %10, %11, %12, %13, %14, %15, "
    "%16, %17, %18, %19, %20, %21, %22, %23, %24, %25, %26, %27, %28, %29, %30, %31, "
    "%32, %33, %34, %35, %36, %37, %38, %39, %40, %41, %42, %43, %44, %45, %46, %47, "
    "%48, %49, %50, %51, %52, %53, %54, %55, %56, %57, %58, %59, %60, %61, %62, %63, "
    "%64, %65, %66, %67, %68, %69, %70, %71, %72, %73, %74, %75, %76, %77, %78, %79, "
    "%80, %81, %82, %83, %84, %85, %86, %87, %88, %89, %90, %91, %92, %93, %94, %95}, "
    "{%96, %97, %98, %99}, %100, p, 1, 1, 1;}"
    : "+f"(d[0]), "+f"(d[1]), "+f"(d[2]), "+f"(d[3]), "+f"(d[4]), "+f"(d[5]), "+f"(d[6]), "+f"(d[7]),
      "+f"(d[8]), "+f"(d[9]), "+f"(d[10]), "+f"(d[11]), "+f"(d[12]), "+f"(d[13]), "+f"(d[14]), "+f"(d[15]),
      "+f"(d[16]), "+f"(d[17]), "+f"(d[18]), "+f"(d[19]), "+f"(d[20]), "+f"(d[21]), "+f"(d[22]), "+f"(d[23]),
      "+f"(d[24]), "+f"(d[25]), "+f"(d[26]), "+f"(d[27]), "+f"(d[28]), "+f"(d[29]), "+f"(d[30]), "+f"(d[31]),
      "+f"(d[32]), "+f"(d[33]), "+f"(d[34]), "+f"(d[35]), "+f"(d[36]), "+f"(d[37]), "+f"(d[38]), "+f"(d[39]),
      "+f"(d[40]), "+f"(d[41]), "+f"(d[42]), "+f"(d[43]), "+f"(d[44]), "+f"(d[45]), "+f"(d[46]), "+f"(d[47]),
      "+f"(d[48]), "+f"(d[49]), "+f"(d[50]), "+f"(d[51]), "+f"(d[52]), "+f"(d[53]), "+f"(d[54]), "+f"(d[55]),
      "+f"(d[56]), "+f"(d[57]), "+f"(d[58]), "+f"(d[59]), "+f"(d[60]), "+f"(d[61]), "+f"(d[62]), "+f"(d[63]),
      "+f"(d[64]), "+f"(d[65]), "+f"(d[66]), "+f"(d[67]), "+f"(d[68]), "+f"(d[69]), "+f"(d[70]), "+f"(d[71]),
      "+f"(d[72]), "+f"(d[73]), "+f"(d[74]), "+f"(d[75]), "+f"(d[76]), "+f"(d[77]), "+f"(d[78]), "+f"(d[79]),
      "+f"(d[80]), "+f"(d[81]), "+f"(d[82]), "+f"(d[83]), "+f"(d[84]), "+f"(d[85]), "+f"(d[86]), "+f"(d[87]),
      "+f"(d[88]), "+f"(d[89]), "+f"(d[90]), "+f"(d[91]), "+f"(d[92]), "+f"(d[93]), "+f"(d[94]), "+f"(d[95])
    : "r"(a[0]), "r"(a[1]), "r"(a[2]), "r"(a[3]), "l"(db), "r"(add));
}
__device__ __forceinline__ void wgmma_n48(float (&d)[24], const uint32_t (&a)[4], uint64_t db, int add) {
  asm volatile("{.reg .pred p; setp.ne.b32 p, %29, 0; wgmma.mma_async.sync.aligned.m64n48k16.f32.bf16.bf16 "
    "{%0, %1, %2, %3, %4, %5, %6, %7, %8, %9, %10, %11, %12, %13, %14, %15, "
    "%16, %17, %18, %19, %20, %21, %22, %23}, "
    "{%24, %25, %26, %27}, %28, p, 1, 1, 1;}"
    : "+f"(d[0]), "+f"(d[1]), "+f"(d[2]), "+f"(d[3]), "+f"(d[4]), "+f"(d[5]), "+f"(d[6]), "+f"(d[7]),
      "+f"(d[8]), "+f"(d[9]), "+f"(d[10]), "+f"(d[11]), "+f"(d[12]), "+f"(d[13]), "+f"(d[14]), "+f"(d[15]),
      "+f"(d[16]), "+f"(d[17]), "+f"(d[18]), "+f"(d[19]), "+f"(d[20]), "+f"(d[21]), "+f"(d[22]), "+f"(d[23])
    : "r"(a[0]), "r"(a[1]), "r"(a[2]), "r"(a[3]), "l"(db), "r"(add));
}
__device__ __forceinline__ void wgmma_n80(float (&d)[40], const uint32_t (&a)[4], uint64_t db, int add) {
  asm volatile("{.reg .pred p; setp.ne.b32 p, %45, 0; wgmma.mma_async.sync.aligned.m64n80k16.f32.bf16.bf16 "
    "{%0, %1, %2, %3, %4, %5, %6, %7, %8, %9, %10, %11, %12, %13, %14, %15, "
    "%16, %17, %18, %19, %20, %21, %22, %23, %24, %25, %26, %27, %28, %29, %30, %31, "
    "%32, %33, %34, %35, %36, %37, %38, %39}, "
    "{%40, %41, %42, %43}, %44, p, 1, 1, 1;}"
    : "+f"(d[0]), "+f"(d[1]), "+f"(d[2]), "+f"(d[3]), "+f"(d[4]), "+f"(d[5]), "+f"(d[6]), "+f"(d[7]),
      "+f"(d[8]), "+f"(d[9]), "+f"(d[10]), "+f"(d[11]), "+f"(d[12]), "+f"(d[13]), "+f"(d[14]), "+f"(d[15]),
      "+f"(d[16]), "+f"(d[17]), "+f"(d[18]), "+f"(d[19]), "+f"(d[20]), "+f"(d[21]), "+f"(d[22]), "+f"(d[23]),
      "+f"(d[24]), "+f"(d[25]), "+f"(d[26]), "+f"(d[27]), "+f"(d[28]), "+f"(d[29]), "+f"(d[30]), "+f"(d[31]),
      "+f"(d[32]), "+f"(d[33]), "+f"(d[34]), "+f"(d[35]), "+f"(d[36]), "+f"(d[37]), "+f"(d[38]), "+f"(d[39])
    : "r"(a[0]), "r"(a[1]), "r"(a[2]), "r"(a[3]), "l"(db), "r"(add));
}

__device__ __forceinline__ constexpr int wo_off(int i) { return (i < 4 ? 8 + i : i - 4) * WO; }
__device__ __forceinline__ void load_stage(const Params& P, uint32_t sb, int st, int j, int g, int rank) {
  const uint32_t fb = sb + OFF_BAR + 8 * (B_FULL + (st & 3)), a = sb + (st & 3) * STAGE;
  mbar_expect_tx(fb, STAGE);
  tma2(a, &P.xa, fb, 640 * rank + 64 * st, 128 * j);
  tma3_both(a + STAGE_A + rank * (STAGE_B0 / 2), &P.w0, fb, 80 * g + 16 * (g & 1), 64 * st + 32 * rank, 0);
  tma3_both(a + STAGE_A + STAGE_B0 + rank * (STAGE_B1 / 2), &P.w1, fb, 80 * g + 64 * (~g & 1), 64 * st + 32 * rank, 0);
}

__device__ __forceinline__ void run_producer(const Params& P, uint8_t* sm, uint32_t sb, int b, uint32_t t0) {
  const int rank = b & 1, g = (b >> 1) & 7, j = b >> 4;
  const uint32_t bar = sb + OFF_BAR;
#pragma unroll 1
  for (int st = 1; st < 10; ++st) {
    if (st == 2) {
      wait_until(t0 + WPF_AT);
      if (elect_one()) bulk_prefetch(P.wqkv + (128 + b) * 1920, 3840);
      bar_sync<NB_GO, 160>();
    }
    if (st == 9) bar_sync<NB_HELP, 128>();
    mbar_wait(bar + 8 * (B_EMPTY + (st & 3)), (((st + 1) >> 2) + 1) & 1);
    if (elect_one()) {
      load_stage(P, sb, st, j, g, rank);
      if (st >= 2 && st < 8) bulk_prefetch(P.wqkv + ((st + 2) * 128 + b) * 960, 1920);
      const int k = st - LMPF_AT;
      if ((uint32_t)k < 5u) bulk_prefetch(P.wmod + (5 * b + k) * 3840 + 1280, 5120);
      if (st == 7) bulk_prefetch(P.wo + b * 3200, 6400);
    }
  }
#pragma unroll 1
  for (int i = 0; i < 8; ++i) {
    if (i < 2 || i == 4 || i == 7) mbar_wait(bar + 8 * (B_EMPTY + (i < 2 ? 2 + i : i & 1)), i == 0);
    if (elect_one()) {
      const uint32_t fb = bar + 8 * (i ? B_WO1 : B_WO0), a = sb + (i < 4 ? 8 + i : i - 4) * WO;
      if (i == 0) {
        mbar_expect_tx(bar + 8 * B_XS, 25600);
        tma2(sb + OFF_LM, &P.wm0, bar + 8 * B_XS, 1280 + 64 * (b & 31), 160 * (b >> 5));
        tma2(sb + OFF_LM + 20480, &P.wm1, bar + 8 * B_XS, 3328 + 16 * (b & 31), 160 * (b >> 5));
      }
      if (i < 2) mbar_expect_tx(fb, i ? 7 * 12800 : 12800);
      if ((i & 1) == rank) {
        const int k0 = 80 * (i ? i - (i <= g) : g);
        tma3_both(a, &P.woa, fb, 80 * g, k0, 0);
        tma2_both(a + 10240, &P.wob, fb, 80 * g + 64, k0);
      }
    }
  }
  if (b < N_FFN) {
    if (elect_one()) {
      mbar_expect_tx(bar + 8 * B_ACT, 1024);
      mbar_expect_tx(bar + 8 * B_FFN, 40960);
    }
    uint32_t next = clock32();
#pragma unroll 1
    for (int i = 0; i < 6; ++i) {
      if (i == FFN_EARLY) {
        mbar_wait(bar + 8 * B_GO, 1);
        next = clock32();
      }
      if (i == 3) bar_sync<NB_LM, 128>();
      if (i == 4) next += DOWN_GAP;
      wait_until(next);
      next += FFN_GAP;
      if (elect_one())
        tma3(sb + OFF_FFN + 10240 * i, &P.wg + (i >> 1), bar + 8 * (i < 4 ? B_FFN : B_XS), i < 4 ? 32 * (b >> 1) : 0, i < 4 ? 0 : 16 * b, i < 4 ? 2 * rank + (i & 1) : 5 * (i & 1));
    }
  }
}

__device__ __forceinline__ void run_helper(const Params& P, uint8_t* sm, uint32_t sb, int b, int hw, uint32_t ep, int budget, uint32_t poll_at) {
  const int h = threadIdx.x - 256, lane = h & 31, gq = lane >> 2, t = lane & 3, rank = b & 1, g = (b >> 1) & 7, j = b >> 4;
  const uint32_t bar = sb + OFF_BAR, prm = sb + OFF_PRM;
  uint4* const box = P.sc + b * BOX;
  const bool main20 = lane < 20;
  const int fin = 128 * (b >> 4) + 16 * ((b >> 2) & 3) + 2 * (b & 3) + (lane & 1) + 32 * (lane & 2) + 2 * (lane & 4);
  const int which = main20 ? 2 - hw : 3, fsl = (fin * 205) >> 14;
  const int q4 = main20 ? lane : min(10 * hw + lane - 20, 19);
  uint32_t wr[2];
  asm volatile("ld.global.nc.v2.u32 {%0, %1}, [%2];" : "=r"(wr[0]), "=r"(wr[1]) : "l"(P.wr + 80 * g + 4 * q4));
  uint32_t cw;
  asm volatile("ld.global.nc.u32 %0, [%1];" : "=r"(cw) : "l"(P.c + 160 * (b >> 5) + 2 * min(h, 79)));
  sts1(sb + OFF_SILU + 4 * min(h, 79), pack2(bf_lo(cw) * sigmoid(bf_lo(cw)), bf_hi(cw) * sigmoid(bf_hi(cw))));
  if (h < 4) sts1(prm + R_ONE + 4 * h, 0x3F803F80u);
  wait_until(poll_at);
  {
    uint32_t v[4][4];
    const int h80 = min(h, 79);
    const uint4* src = at<16>(P.sc + TABLES, 320 * j + h80);
#pragma unroll 1
    do {
#pragma unroll
      for (int i = 0; i < 4; ++i) ld_rlx4(v[i], src + i * 80);
    } while (retry<~0u>(stale<4, 2>(v, ep), budget));
#pragma unroll
    for (int i = 0; i < 4; ++i) sts2(sb + OFF_C1 + 16 * h80 + 1280 * (i & 1) + (i < 2 ? 8 : 0), v[i][0], v[i][1]);
    mbar_arrive(bar + 8 * B_TAB);
  }
  bar_sync<NB_GO, 160>();
  {
    const char* src = hw == 2 ? at<128>(reinterpret_cast<const char*>(P.wdown), 160 * b + lane)
                              : at<128>(reinterpret_cast<const char*>(hw ? P.wup : P.wgate), (160 * (b & 3) + lane) * 27 + (b >> 2));
    uint4* slot = at<16>(box + M_HALO, h);
    uint32_t next = clock32() + TOUCH_AT + hw * (TOUCH_GAP / 3);
#pragma unroll 1
    for (int i = 0; i < 5; ++i) {
      wait_until(next);
      next += TOUCH_GAP;
      if (b < N_FFN) asm volatile("cp.async.cg.shared.global.L2::128B [%0], [%1], 16;" ::"r"(sb + OFF_SINK + 16 * h), "l"(src) : "memory");
      src += hw == 2 ? 4096 : 32 * 3456;
      if (i < 4) {
        st_rlx4(slot, ~ep, ~ep, ~ep, ~ep);
        st_rlx4(slot + 96, ~ep, ~ep, ~ep, ~ep);
      }
      slot += 192;
    }
  }
  bar_sync<NB_HELP, 128>();

  {
    float d0[4] = {0.f, 0.f, 0.f, 0.f}, d1[4] = {0.f, 0.f, 0.f, 0.f};
    const uint32_t row = 8 * (lane >> 4) + (lane & 7), half = (lane >> 3) & 1, kstep = hw < 2 ? 2048 : 512;
    uint32_t wa = sb + OFF_LM + (hw < 2 ? row * 128 + (((4 * hw + half) ^ (lane & 7)) << 4) : 20480 + row * 32 + ((half ^ ((lane >> 2) & 1)) << 4)), sa = sb + OFF_SILU + (lane >> 3) * 16;
    mbar_wait(bar + 8 * B_XS, 1);
    {
      uint32_t hv[2][4] = {};
      const int q = min(2 * hw, 3);
      const uint4* const src = at<16>(box + (M_HALO - 16 * BOX), 32 * q + lane);
      mbar_wait(bar + 8 * B_EMPTY, 0);
      wait_until(clock32() + HALO_GAP);
      if (j > 0) gather<2, 32, 0>(hv, src, ep, budget);
      stsm4(sb + OFF_H + 512 * q + 16 * lane, hv[0]);
      stsm4(sb + OFF_H + 512 * q + 16 * lane + 512, hv[1]);
      bar_arrive<NB_HALO, 128>();
    }
    mbar_wait(bar + 8 * (B_EMPTY + 1), 0);
    const uint32_t o1 = hw < 2 ? (wa ^ 32) - wa : 1024, s1 = hw < 2 ? 0 : 64;
#pragma unroll 1
    for (int u = hw < 2 ? 0 : 2; u < 5; ++u) {
      uint32_t a[4][4], s[2][4];
      ldsm4(s[0], sa);
      ldsm4t(a[0], wa);
      ldsm4t(a[1], wa + o1);
      ldsm4(s[1], sa + s1);
      ldsm4t(a[2], wa + kstep);
      ldsm4t(a[3], wa + kstep + o1);
      sched_fence(P.zero);
      mma16(d0, a[0], s[0][0], s[0][1], d0);
      if (hw < 2 || u < 4) mma16(d1, a[1], s[1][0], s[1][1], d1);
      mma16(d0, a[2], s[0][2], s[0][3], d0);
      if (hw < 2 || u < 4) mma16(d1, a[3], s[1][2], s[1][3], d1);
      wa += hw < 2 ? 4096 : 2048;
      sa += 64 + s1;
    }
    if (hw == 2) {
      d0[0] += d1[0];
      d0[2] += d1[2];
    }
    const float v = t & 2 ? (t & 1 ? d1[2] : d1[0]) : (t & 1 ? d0[2] : d0[0]);
    if (32 * hw + 8 * t < 80) st_rlx1(at<4>(box + M_LATE, 32 * hw + 8 * t + gq), tag(u32(v), ep));
  }
  if (b < N_FFN) {
    if (h == 0) mbar_expect_tx(bar + 8 * B_XS, 20480);
    bar_arrive<NB_LM, 128>();
  }
  wait_until(clock32() + LATE_GAP);
  {
    uint32_t v[4][4];
    const int q = 160 * which + (main20 || hw < 2 ? 20 * g + q4 : min(fin >> 2, 159));
    const uint4* src = at<16>(P.sc + M_LATE, q < 512 ? (q >> 4) * BOX + (q & 15) : ((q - 512) >> 2) * BOX + 16 + (q & 3));
#pragma unroll 1
    do {
#pragma unroll
      for (int i = 0; i < 4; ++i) ld_rlx4(v[i], src + i * 32 * BOX);
    } while (retry<1>(stale<4, 0>(v, ep) | stale<4, 1>(v, ep) | stale<4, 2>(v, ep) | stale<4, 3>(v, ep), budget));
    const uint32_t one = which == 2 ? 0x3F803F80u : 0u;
    uint32_t w[2], pw[2];
#pragma unroll
    for (int e = 0; e < 2; ++e) {
      w[e] = fma2(pack2(f32(v[0][2 * e]) + f32(v[1][2 * e]) + f32(v[2][2 * e]) + f32(v[3][2 * e]),
                        f32(v[0][2 * e + 1]) + f32(v[1][2 * e + 1]) + f32(v[2][2 * e + 1]) + f32(v[3][2 * e + 1])), 0x3F803F80u, one);
      pw[e] = fma2(w[e], wr[e], 0x80008000u);
    }
    const uint32_t dst = prm + (main20 || hw < 2 ? 160 * which + 8 * q4 : R_FIN + 4 * (lane & 6));
    sts2(dst, w[0], w[1]);
    sts2(dst + 800, pw[0], pw[1]);
    float s = main20 ? bf_lo(pw[0]) + bf_hi(pw[0]) + bf_lo(pw[1]) + bf_hi(pw[1]) : 0.f;
#pragma unroll
    for (int o = 16; o > 0; o >>= 1) s += shx(s, o);
    sts1(sb + OFF_KEY + 64 + 4 * hw, u32(s));
    mbar_arrive(bar + 8 * B_TAB);
    mbar_wait(bar + 8 * B_TAB, 1);
  }

  uint32_t ckey = 0;
  uint4* const odst = reinterpret_cast<uint4*>(P.out + (256 * j + rank) * 640 + 80 * g);
  if (hw == 0) {
    const uint32_t tile = min(4 * (lane & 3) + (lane >> 3), 9) * 16;
    uint32_t c1[4], sv[4], gb[4], x[4];
    ldsm4(c1, prm + R_C1 + tile);
    ldsm4(sv, prm + R_SB + tile);
    ldsm4(gb, prm + (lane & 4 ? R_GB + tile : R_ONE));
    const uint32_t bc = lds1(sb + OFF_KEY + 68), keep = lop3<0xF0>(gq & 4 ? ~0u : 0u, 0u, 0u);
    uint4* const cdst = at<16>(P.sc + M_CAND, (b - rank + (lane >> 4)) * BOX + 2 * (lane & 12) + 4 * rank + (lane & 3));
    uint32_t crow;
    {
      sched_fence(P.zero);
      bar_sync<NB_KEY, 288>();
      uint32_t k4[4];
      lds4(k4, sb + OFF_ROWS + 16 * lane);
      ckey = __reduce_max_sync(0xFFFFFFFFu, max(max(k4[0], k4[1]), max(k4[2], k4[3])));
      crow = (~ckey >> 1) & 127;
      const uint32_t nw = lds1(sb + OFF_ROWS + 512 + 4 * crow);
      ldsm4(x, sb + OFF_X2 + crow * 176 + tile);
      const uint32_t rs = dup_hi(nw), nm = dup_lo(nw);
#pragma unroll
      for (int e = 0; e < 4; ++e) x[e] = fma2(gb[e], fma2(fma2(x[e], rs, nm), c1[e], sv[e]), x[e] & keep);
      st_rlx4(cdst, tag(x[0], ep), x[1], gq == 2 ? ckey : x[2], gq == 2 ? bc : x[3]);
    }
    bar_arrive<NB_PUB, 288>();
    bar_sync<NB_OUT + 1, 160>();
    uint32_t next = clock32() + OUT_AT;
#pragma unroll 1
    for (int u = 0; u < 8; ++u) {
      if (u == 4) {
        bar_sync<NB_OUT, 160>();
        next = clock32();
      }
      wait_until(next);
      next += OUT_GAP;
      if (u != crow >> 4 && elect_one())
        asm volatile("cp.async.bulk.tensor.2d.global.shared::cta.bulk_group [%0, {%2, %3}], [%1];"
                     ::"l"(&P.om), "r"(sb + OFF_OUT + 2560 * u), "r"(640 * rank + 80 * g), "r"(128 * j + 16 * u) : "memory");
    }
    asm volatile("cp.async.bulk.commit_group;" ::: "memory");
  } else {
    if (b >= 80 || hw == 2) return;
    bar_sync<NB_WIN, 64>();
  }
  uint32_t m[7][4], wkey = lds1(sb + OFF_KEY + 80);
  if (b >= N_FFN) {
    gather<1, 0, 0>(m, at<64>(P.sc + M_CAND + 16, (lane & 14) * (2 * BOX) + (lane & 1)), ep, budget);
    wkey = __reduce_max_sync(0xFFFFFFFFu, m[0][2]);
  }
  const uint32_t wtok = ~wkey & 2047;
  if (hw == 0) {
    const uint32_t u = (~ckey >> 5) & 7, skip = ckey == wkey ? (~ckey >> 1) & 15 : 16;
#pragma unroll
    for (int i = 0; i < 5; ++i) {
      const uint32_t v = lane + 32 * i, r = (v * 205) >> 11;
      if (r != skip) *at<16>(odst, 2560 * u + v + 150 * r) = *reinterpret_cast<const uint4*>(sm + OFF_OUT + 2560 * u + 16 * v);
    }
    st_rlx1(at<4>(box + M_EPOCH, lane), ep);
    asm volatile("cp.async.bulk.wait_group.read 0;" ::: "memory");
    return;
  } else {
    const int cn = fin - 80 * fsl;
    gather<1, 0, 0>(m, at<16>(P.sc + M_CAND, (16 * (wtok >> 8) + (lane & 8 ? 2 * (lane & 7) : 2 * fsl + 1)) * BOX + 4 * (wtok & 1) +
                                             (lane & 8 ? 16 : 8 * (cn >> 5) + ((cn >> 1) & 3))), ep, budget);
    const uint32_t bw = cn & 16 ? (cn & 8 ? m[0][3] : m[0][2]) : (cn & 8 ? m[0][1] : m[0][0]);
    const uint32_t gw = lds1(prm + R_FIN + 4 * (lane & 6) + 4 * (b & 1));
    float r = f32(m[0][3]);
#pragma unroll
    for (int o = 1; o < 8; o <<= 1) r += shx(r, o);
    r = __shfl_sync(0xFFFFFFFFu, r, 8) + f32(wkey >> 31 ? wkey & 0x7FFFF800u : ~wkey | 0x7FFu);
    const float sg = bf_round(sigmoid(bf_round(r))), gv = lane & 1 ? bf_hi(gw) : bf_lo(gw), bv = lane & 1 ? bf_hi(bw) : bf_lo(bw);
    __nv_bfloat16* const dst = at<2>(P.out, wtok * 640 + fin);
    const uint4* const src = at<16>(P.sc + M_YP, (4 * (lane >> 3) + ((b >> 2) & 3)) * BOX + 32 * j + 8 * (b & 3) + (lane & 7));
    bar_sync<NB_YP, 64>();
    wait_until(clock32() + YP_GAP);
    gather_lazy<7, 16 * BOX, 32 * BOX, 0>(m, src, ep, budget, lane >= 24);
    float y[4];
#pragma unroll
    for (int e = 0; e < 4; ++e)
      y[e] = ((f32(m[0][e]) + f32(m[1][e])) + (f32(m[2][e]) + f32(m[3][e]))) + ((f32(m[4][e]) + f32(m[5][e])) + f32(m[6][e]));
    const bool u1 = lane & 2, u2 = lane & 4;
    const float e0 = (u1 ? y[1] : y[0]) + shx(u1 ? y[0] : y[1], 2), e1 = (u1 ? y[3] : y[2]) + shx(u1 ? y[2] : y[3], 2);
    float e = (u2 ? e1 : e0) + shx(u2 ? e0 : e1, 4);
    e += shx(e, 8);
    e += shx(e, 16);
    asm volatile("{.reg .pred p; setp.lt.u32 p, %2, 8; @p st.global.b16 [%0], %1;}"
                 ::"l"(dst), "h"((uint16_t)pack2(fmaf(gv, bf_round(bf_round(e) * sg), bv), 0.f)), "r"(lane) : "memory");
  }
}

template <int ODD> __device__ __forceinline__ uint32_t pack_acc(const float (&a)[96], const float (&b)[24], int part, int i, int h) {
  const int r = (i + 8 * ODD) % 10;
  const float* const v = r < 8 ? a + 32 * part + 4 * r : b + 8 * part + 4 * (r & 1);
  return pack2(v[2 * h], v[2 * h + 1]);
}
template <int V> struct Int { static constexpr int v = V; };
__device__ __forceinline__ constexpr int kpos(int i) { return i == 2 ? 8 : i == 7 ? 9 : i - (i > 2) - (i > 7); }

__device__ __forceinline__ void run_consumer(const Params& P, uint8_t* sm, uint32_t sb, int b, int warp, uint32_t ep, int budget) {
  const int tid = keep(threadIdx.x ^ 2), lane = tid & 31, gq = lane >> 2, t = lane & 3, p = warp >> 2, wq = warp & 3, rb = warp ^ 4;
  const int rank = b & 1, g = (b >> 1) & 7, j = b >> 4;
  const uint32_t bar = sb + OFF_BAR;
  uint4* const box = P.sc + b * BOX;
  const float z4[4] = {0.f, 0.f, 0.f, 0.f};

  uint32_t nrm[4];
  {
    uint32_t x[5][4], ones[10];
#pragma unroll
    for (int i = 0; i < 10; ++i) ones[i] = 0x3F803F80u;
    uint4* const dst = at<8>(box + M_ST1, tid >> 4);
    mbar_wait(bar + 8 * B_XS, 0);
    asm volatile("cp.async.wait_all;" ::: "memory");
#pragma unroll
    for (int i = 0; i < 5; ++i) lds4(x[i], sb + OFF_XS + 4096 * i + 16 * tid);
    float s[4], qlo, qhi, mean, rstd;
    row_stats(s, qlo, qhi, x, ones, gq);
    const float q = __shfl_sync(0xFFFFFFFFu, qlo + qhi, 4 * gq + (gq >> 1));
    float v = t & 1 ? q : s[0] + s[2];
    v += shx(v, 4);
    v += shx(v, 8);
    const uint32_t nw = norm_word(v, shx(v, 1), mean, rstd);
    if ((lane & 15) == 0) st_rlx2(dst, nw, ep);
    asm volatile("setmaxnreg.inc.sync.aligned.u32 224;");
  }

  float accA[96], accB[24];
#pragma unroll
  for (int i = 0; i < 96; ++i) asm volatile("" : "=f"(accA[i]));
#pragma unroll
  for (int i = 0; i < 24; ++i) asm volatile("" : "=f"(accB[i]));
  uint32_t xr[5][4];
#pragma unroll
  for (int i = 0; i < 20; ++i) asm volatile("" : "=r"(xr[i >> 2][i & 3]));
  const uint32_t turn = keep(NB_TURN + (tid >> 7)), pass = keep(NB_TURN + 1 - (tid >> 7));
  uint4* const opub = reinterpret_cast<uint4*>(__shfl_xor_sync(0xFFFFFFFFu, reinterpret_cast<uintptr_t>(at<16>(box + M_O, tid ^ 2)), 2));
  const uint4* src[7];
  const uint4* const lower = reinterpret_cast<const uint4*>(__shfl_xor_sync(0xFFFFFFFFu, reinterpret_cast<uintptr_t>(at<16>(P.sc + M_O, (b & ~14) * BOX + (tid ^ 2))), 2));
  const int l2 = lane ^ 2;
  const uint32_t ha = keep(sb + OFF_H + rb * 2560 + 16 * l2), lo = keep(sb + OFF_L + rb * 1280 + 16 * l2);
  const uint32_t va = keep(sb + OFF_H + 1280 + (rb + ((lane >> 3) & 1)) * 2560 + (lane >> 4) * 128 + (l2 & 7) * 16);
  const uint32_t M = keep((2 * (t ^ 2) > gq ? 0xFFFFu : 0u) | (2 * (t ^ 2) + 1 > gq ? 0xFFFF0000u : 0u)), gk = keep(g + (tid >> 9));
  {
    uint32_t la[4], raw[4][4], cw[4][4];
#pragma unroll
    for (int k = 0; k < 4; ++k) la[k] = keep(sb + (16 * rb + (l2 & 15)) * 128 + (((lane >> 4) ^ (l2 & 7) ^ (2 * k)) << 4));
    const uint32_t rel = keep(map_to_cta(bar + 8 * B_EMPTY, lane & 1)), c1a = keep(sb + OFF_C1 + 16 * (t ^ 2));
    const bool two = (ha & 0x1E0) == 0;
    constexpr uint64_t d0 = make_desc(SMEM_BASE + STAGE_A, 4096, 1024, 1), d1 = make_desc(SMEM_BASE + STAGE_A + STAGE_B0, 1024, 256, 3);
    const auto pick_x = [&](int st) {
#pragma unroll
      for (int k = 0; k < 4; ++k)
        if (g == (4 * st + k) / 5) ldsm4(xr[(4 * st + k) % 5], la[k] + (st & 3) * STAGE);
    };
    if (p == 1) turn_pass(pass);
    {
      const uint4* const src = at<8>(P.sc + M_ST1, (16 * j + 2 * rb) * 2 * BOX + 2 * gq + rank);
      mbar_wait(bar + 8 * B_FULL, 0);
#pragma unroll
      for (int k = 0; k < 4; ++k) ldsm4(raw[k], la[k]);
      pick_x(0);
      uint32_t n0[2], n1[2];
#pragma unroll 1
      do {
        ld_rlx2(n0, src);
        ld_rlx2(n1, src + BOX);
      } while (retry<~0u>(neq2(n0[1], n1[1], ep), budget));
      mbar_wait(bar + 8 * B_TAB, 0);
      if (warp == 0) bar_arrive<NB_GO, 160>();
#pragma unroll
      for (int k = 0; k < 4; ++k) lds4(cw[k], c1a + 64 * k);
      nrm[0] = dup_hi(n0[0]); nrm[1] = dup_hi(n1[0]); nrm[2] = dup_lo(n0[0]); nrm[3] = dup_lo(n1[0]);
    }
#pragma unroll
    for (int st = 0; st < 10; ++st) {
      uint32_t af[4][4];
#pragma unroll
      for (int k = 0; k < 16; ++k) raw[k >> 2][k & 3] = fma2(raw[k >> 2][k & 3], nrm[k & 1], nrm[2 + (k & 1)]);
      if (st) wg_wait();
      if (two) mbar_arrive_cluster(rel + 8 * ((st + 3) & 3));
#pragma unroll
      for (int k = 0; k < 16; ++k) af[k >> 2][k & 3] = fma2(raw[k >> 2][k & 3], cw[k >> 2][(k >> 1) & 1], cw[k >> 2][2 + ((k >> 1) & 1)]);
      if (st < 9) {
#pragma unroll
        for (int k = 0; k < 4; ++k) lds4(cw[k], c1a + 256 * (st + 1) + 64 * k);
      }
      wg_fence();
      turn_wait(turn);
#pragma unroll
      for (int k = 0; k < 4; ++k) {
        wgmma_n192(accA, af[k], d0 + ((st & 3) * STAGE + (k >> 1) * (STAGE_B0 / 2) + (k & 1) * 2048 >> 4), k + st);
        if (PASS1 == 2 * k) turn_pass(pass);
        wgmma_n48(accB, af[k], d1 + ((st & 3) * STAGE + (k >> 1) * (STAGE_B1 / 2) + (k & 1) * 512 >> 4), k + st);
        if (PASS1 == 2 * k + 1) turn_pass(pass);
      }
      wg_commit();
      if (st < 9) {
        mbar_wait(bar + 8 * ((st + 1) & 3), ((st + 1) >> 2) & 1);
#pragma unroll
        for (int k = 0; k < 4; ++k) ldsm4(raw[k], la[k] + ((st + 1) & 3) * STAGE);
        pick_x(st + 1);
      }
    }
    wg_wait();
    if (two) mbar_arrive_cluster(rel + 8);
  }

  uint32_t o[5][4];
  {
    uint32_t hi[20], vl[10], kl[10], kh[10], vv[20], qf[4][4], qs[4][2];
    const auto pack_hi = [&](auto odd) {
#pragma unroll
      for (int i = 0; i < 10; ++i) {
        hi[kpos(i)] = pack_acc<odd.v>(accA, accB, 1, i, 1);
        hi[10 + i] = pack_acc<odd.v>(accA, accB, 2, i, 1);
      }
    };
    const auto pack_rest = [&](auto odd) {
#pragma unroll
      for (int i = 0; i < 10; ++i) {
        kl[kpos(i)] = pack_acc<odd.v>(accA, accB, 1, i, 0);
        vl[i] = pack_acc<odd.v>(accA, accB, 2, i, 0);
      }
#pragma unroll
      for (int i = 0; i < 16; ++i) qf[i >> 2][i & 3] = pack_acc<odd.v>(accA, accB, 0, 5 * (i >> 3) + 3 * ((i >> 2) & 1) + ((i >> 1) & 1), i & 1);
#pragma unroll
      for (int i = 0; i < 4; ++i) qs[i | 1][i & 1] = pack_acc<odd.v>(accA, accB, 0, 5 * (i >> 1) + 2, i & 1);
    };
    const auto stage = [&]() {
#pragma unroll
      for (int q = 0; q < 5; ++q) stsm4(ha + 2560 + 512 * q, hi + 4 * q);
      stsm4(lo, vl);
      stsm4(lo + 512, vl + 4);
      stsm2(lo + 1024, vl + 8);
    };
    const auto pack_all = [&](auto odd) {
      pack_hi(odd);
#pragma unroll
      for (int q = 0; q < 5; ++q) hi[4 * q] = tag(hi[4 * q], ep);
      if (rb == 7) {
#pragma unroll
        for (int q = 0; q < 5; ++q) st_rlx4(opub + (M_HALO - M_O - 96 + 32 * q), hi + 4 * q);
      }
      sched_fence(P.zero);
      pack_rest(odd);
      stage();
    };
    if (g & 1) pack_all(Int<1>());
    else pack_all(Int<0>());
#pragma unroll
    for (int i = 0; i < 8; ++i) qs[i >> 1][i & 1] = (t >> 1) == ((i >> 1) & 1) ? qs[(i >> 1) | 1][i & 1] : 0u;
    __syncwarp();
    if (lane == 0) mbar_arrive(bar + 8 * B_HALO);
    float S0[4][4], S1[4][4], S2[4][4];
    ldsm4t(vl, lo);
    ldsm4t(vl + 4, lo + 512);
    ldsm2t(vl + 8, lo + 1024);
    sched_fence(P.zero);
#pragma unroll
    for (int hd = 0; hd < 4; ++hd) {
      mma16(S1[hd], qf[hd], kl[2 * hd], kl[2 * hd + 1], z4);
      mma16(S2[hd], qf[hd], hi[2 * hd], hi[2 * hd + 1], z4);
    }
#pragma unroll
    for (int hd = 0; hd < 4; ++hd) {
      mma8(S1[hd], qs[hd][0], qs[hd][1], kl[8 + (hd >> 1)], S1[hd]);
      mma8(S2[hd], qs[hd][0], qs[hd][1], hi[8 + (hd >> 1)], S2[hd]);
    }
    const bool up0 = M == ~0u, up1 = M != 0;
    uint32_t pp[4][2];
    const auto softmax = [&](const float (&A)[4][4], const float (&B)[4][4], int e) {
      const float SC = 0.22360679774997896f * 1.4426950408889634f;
      float a[4][2], mx[4];
#pragma unroll
      for (int hd = 0; hd < 4; ++hd) {
        a[hd][0] = up0 ? A[hd][2 * e] : B[hd][2 * e];
        a[hd][1] = up1 ? A[hd][2 * e + 1] : B[hd][2 * e + 1];
        mx[hd] = fmaxf(a[hd][0], a[hd][1]);
      }
#pragma unroll
      for (int s = 1; s < 4; s <<= 1) {
#pragma unroll
        for (int hd = 0; hd < 4; ++hd) mx[hd] = fmaxf(mx[hd], shx(mx[hd], s));
      }
#pragma unroll
      for (int hd = 0; hd < 4; ++hd) {
        const float ms = mx[hd] * -SC;
        pp[hd][e] = pack2(ex2(fmaf(a[hd][0], SC, ms)), ex2(fmaf(a[hd][1], SC, ms)));
      }
    };
#pragma unroll
    for (int i = 0; i < 7; ++i)
      asm volatile("{.reg .pred p; setp.gt.u32 p, %1, %2; selp.b64 %0, %3, %4, p;}" : "=l"(src[i]) : "r"(gk), "r"(i), "l"(lower), "l"(lower + 2 * BOX));
    mbar_wait(bar + 8 * B_HALO, 0);
    if (rb == 0) bar_sync<NB_HALO, 128>();
    ldsm4(kh, ha);
    ldsm4(kh + 4, ha + 512);
    ldsm2(kh + 8, ha + 1024);
#pragma unroll
    for (int i = 0; i < 5; ++i) ldsm4t(vv + 4 * i, va + 256 * i);
    const float ev = (j | rb) == 0 ? -1e9f / 0.22360679774997896f : 0.f, e4[4] = {ev, ev, ev, ev};
#pragma unroll
    for (int hd = 0; hd < 4; ++hd) mma16(S0[hd], qf[hd], kh[2 * hd], kh[2 * hd + 1], e4);
#pragma unroll
    for (int hd = 0; hd < 4; ++hd) mma8(S0[hd], qs[hd][0], qs[hd][1], kh[8 + (hd >> 1)], S0[hd]);
    softmax(S1, S2, 1);
    softmax(S0, S1, 0);
    float L[4][4], O[4][3][4];
#pragma unroll
    for (int hd = 0; hd < 4; ++hd) mma8(L[hd], pp[hd][0], pp[hd][1], 0x3F803F80u, z4);
#pragma unroll
    for (int hd = 0; hd < 4; ++hd) {
      const uint32_t p0 = pp[hd][0] & M, p2 = pp[hd][0] & ~M, p3 = pp[hd][1] & M, p5 = pp[hd][1] & ~M;
      const uint32_t z0 = pp[hd][0] & P.zero, z1 = pp[hd][1] & P.zero;
#pragma unroll
      for (int e = 0; e < 3; ++e) {
        const int f = 5 * (hd >> 1) + 2 * (hd & 1) + e;
        mma16(O[hd][e], p0, z0, z1, p5, vv[2 * f], vv[2 * f + 1], z4);
      }
#pragma unroll
      for (int e = 0; e < 3; ++e) mma8(O[hd][e], p2, p3, vl[5 * (hd >> 1) + 2 * (hd & 1) + e], O[hd][e]);
    }
    const bool odd = t >> 1;
#pragma unroll
    for (int hp = 0; hp < 2; ++hp) {
      const float (&A)[3][4] = O[2 * hp];
      const float (&B)[3][4] = O[2 * hp + 1];
#pragma unroll
      for (int e = 0; e < 2; ++e) {
        const float ra = rcp(L[2 * hp][2 * e]), rc = rcp(L[2 * hp + 1][2 * e]), rm = odd ? rc : ra;
        uint32_t* const d = &o[0][0] + 10 * hp + e;
        d[0] = pack2(A[0][2 * e] * ra, A[0][2 * e + 1] * ra);
        d[2] = pack2(A[1][2 * e] * ra, A[1][2 * e + 1] * ra);
        d[4] = pack2((odd ? B[0][2 * e] : A[2][2 * e]) * rm, (odd ? B[0][2 * e + 1] : A[2][2 * e + 1]) * rm);
        d[6] = pack2(B[1][2 * e] * rc, B[1][2 * e + 1] * rc);
        d[8] = pack2(B[2][2 * e] * rc, B[2][2 * e + 1] * rc);
      }
      if (hp == 0) {
#pragma unroll
        for (int s = 0; s < 2; ++s) {
          o[s][0] = tag(o[s][0], ep);
          st_rlx4(opub + 256 * s, o[s]);
        }
        sched_fence(P.zero);
        if (p == 1) bar_arrive<NB_PV, 256>();
      }
    }
#pragma unroll
    for (int s = 2; s < 5; ++s) o[s][0] = tag(o[s][0], ep);
  }

  float acc[40];
#pragma unroll
  for (int i = 0; i < 40; ++i) asm volatile("" : "=f"(acc[i]));
  uint32_t ga[10], pb[10], uw;
  uint4* const sdst = at<16>(box + M_ST2, 16 * rb + gq);
  const uint32_t prow = sb + OFF_PRM + (lane >> 3) * 16;
  {
    const uint64_t dw = make_desc(sb, 5120, 512, 2);
    uint32_t in[5][7][4];
    const auto fetch = [&](int s) {
#pragma unroll
      for (int i = 0; i < 7; ++i) ld_rlx4(in[s][i], src[i] + (2 * BOX * i + 256 * s));
    };
    st_rlx4(opub + 256 * 2, o[2]);
    mbar_wait(bar + 8 * B_WO0, 0);
    if (p == 0) bar_sync<NB_PV, 256>();
    fetch(0);
    wg_fence();
    turn_wait(turn);
#pragma unroll
    for (int s = 0; s < 5; ++s) {
      wgmma_n80(acc, o[s], dw + (wo_off(0) + 1024 * s >> 4), s);
      if (s == PASS0) turn_pass(pass);
    }
    wg_commit();
    mbar_wait(bar + 8 * B_WO1, 0);
    sched_fence(P.zero);
#pragma unroll 1
    while (retry<1>(stale<7, 0>(in[0], ep), budget)) {
#pragma unroll
      for (int i = 0; i < 7; ++i) ld_rlx4_stale(in[0][i], src[i] + 2 * BOX * i, in[0][i][0], ep);
    }
    fetch(1);
    st_rlx4(opub + 256 * 3, o[3]);
    st_rlx4(opub + 256 * 4, o[4]);
#pragma unroll
    for (int s = 0; s < 5; ++s) {
      if (s == FGO_STEP && tid == 128) mbar_arrive(bar + 8 * B_GO);
      wg_fence();
      turn_wait(turn);
#pragma unroll
      for (int i = 0; i < 7; ++i) {
        wgmma_n80(acc, in[s][i], dw + (wo_off(i + 1) + 1024 * s >> 4), 1);
        if (i == PASS_AT - 1) {
          if (s < 4 || p == 0) turn_pass(pass);
          if (s == 4) {
            wg_commit();
            wg_fence();
          }
          if (s + AHEAD > 1 && s + AHEAD < 5) {
            wg_commit();
            asm volatile("wgmma.wait_group.sync.aligned %0;" ::"n"(AHEAD == 1 ? 3 : 1) : "memory");
            fetch(s + AHEAD);
            wg_fence();
          }
        }
      }
      wg_commit();
    }
    sched_fence(P.zero);
    asm volatile("wgmma.wait_group.sync.aligned 2;" ::: "memory");
    mbar_wait(bar + 8 * B_TAB, 1);
    ld_row(ga, prow + R_GA);
    ldsm4(pb, lane & 1 ? prow + R_P : sb + OFF_PRM + R_ONE);
    ldsm4(pb + 4, lane & 1 ? prow + R_P + 64 : sb + OFF_PRM + R_ONE);
    ldsm2(pb + 8, lane & 1 ? prow + R_P + 128 : sb + OFF_PRM + R_ONE);
    uw = tag(lds1(sb + OFF_KEY + 64), ep);
    const uint32_t bad = stale<28, 0>(in[1], ep);
    uint32_t redo;
    asm volatile("{.reg .pred p; setp.ne.u32 p, %1, 0; barrier.cta.red.or.aligned.pred p, %2, 128, p; selp.u32 %0, 1, 0, p;}"
                 : "=r"(redo) : "r"(bad & 1u), "r"(turn + (NB_REDO - NB_TURN)) : "memory");
    if (redo) {
#pragma unroll 1
      for (int q = 0; q < 40; ++q) {
        const int i = q & 7, s = q >> 3;
        uint32_t a[1][4];
        wg_wait();
        gather<1, 0, 0>(a, lower + (2 * BOX * (i ? i - (i <= g) : g) + 256 * s), ep, budget);
        wg_fence();
        wgmma_n80(acc, a[0], dw + ((i < 4 ? 8 + i : i - 4) * WO + 1024 * s >> 4), q);
        wg_commit();
      }
    }
    wg_wait();
  }

  uint32_t c1[10], sv[10], gb[10], nw;
  const uint32_t trow = 16 * rb + (lane & 15), xt = sb + (lane >> 4) * 16;
  {
#pragma unroll
    for (int k = 0; k < 20; ++k) acc2(xr[k >> 2][k & 3], ga[k >> 1], pack2(acc[2 * k], acc[2 * k + 1]));
    float s[4], qlo, qhi;
    row_stats(s, qlo, qhi, xr, pb, gq);
    if (t == gq >> 1) {
      st_rlx4(sdst, u32(s[0]), u32(s[1]), u32(qlo), uw);
      st_rlx4(sdst + 8, u32(s[2]), u32(s[3]), u32(qhi), uw);
    }
    sched_fence(P.zero);
    const uint32_t tok = keep(256 * j + 32 * rb + (l2 & 30) + rank), kdst = keep(sb + OFF_ROWS + 64 * rb + 2 * (l2 & 30) + 512 * (lane & 1));
#pragma unroll
    for (int s5 = 0; s5 < 5; ++s5) stsm4(xt + trow * 176 + (OFF_X2 + 32 * s5), xr[s5]);
    uint32_t m[4][4];
    ld_row(c1, prow + R_C1);
    ld_row(sv, prow + R_SB);
    ld_row(gb, prow + R_GB);
    gather_lazy<4, 2 * BOX, 4 * BOX, 3>(m, at<16>(P.sc + M_ST2, (16 * j + rank + 8 * (lane & 1)) * BOX + 16 * rb + (lane >> 1)), ep, budget);
#pragma unroll
    for (int e = 0; e < 4; ++e) {
      s[e] = (f32(m[0][e]) + f32(m[1][e])) + (f32(m[2][e]) + f32(m[3][e]));
      s[e] += shx(s[e], 1);
    }
    float mean, rstd;
    nw = norm_word(s[0], s[2], mean, rstd);
    const uint32_t u = u32(rstd * fmaf(-mean, s[3], s[1]));
    const uint32_t key = ((u ^ ((uint32_t)((int)u >> 31) | 0x80000000u)) | 2047u) ^ tok;
    sts1(kdst, lane & 1 ? nw : key);
    bar_arrive<NB_KEY, 288>();
    bar_sync<NB_PUB, 288>();
  }

  if (p == 0 && b < N_FFN) {
    uint32_t wf[20][4], m[6][4];
    mbar_wait(bar + 8 * B_FFN, 1);
#pragma unroll
    for (int i = 0; i < 20; ++i)
      ldsm4t(wf[i], sb + OFF_FFN + (lane & 8) * 2560 + (80 * wq + 8 * (lane >> 4) + (lane & 7)) * 64 + (((i & 3) ^ ((lane >> 1) & 3)) << 4) + 1024 * (i >> 2));
    const uint32_t far = map_to_cta(sb, 0), dst = far + OFF_ACT + (4 * rank + wq) * 128 + gq * 16, step = map_to_cta(sb, 1) - far;
    gather_lazy<6, 64 * BOX, 8, 0>(m, at<16>(P.sc + M_CAND, (8 * (gq & 6) + 8 * rank + 2 * wq) * BOX + (lane & 7)), ep, budget);
    const bool second = m[5][2] > m[4][2];
    const uint32_t wtok = ~__reduce_max_sync(0xFFFFFFFFu, max(m[4][2], m[5][2]));
    float f[4][4];
#pragma unroll
    for (int s = 0; s < 5; ++s) {
      const uint32_t b0 = second ? m[(s & 6) + 1][2 * (s & 1)] : m[s & 6][2 * (s & 1)], b1 = second ? m[(s & 6) + 1][2 * (s & 1) + 1] : m[s & 6][2 * (s & 1) + 1];
#pragma unroll
      for (int mt = 0; mt < 4; ++mt) mma16(f[mt], wf[4 * s + mt], b0, b1, s ? f[mt] : z4);
    }
    if (t == ((wtok >> 8) & 3)) {
      const bool e = wtok & 1;
#pragma unroll
      for (int r = 0; r < 2; ++r)
        asm volatile("st.async.weak.shared::cluster.mbarrier::complete_tx::bytes.v4.f32 [%0], {%1, %2, %3, %4}, [%5];"
                     ::"r"(dst + r * step), "f"(e ? f[2 * r][1] : f[2 * r][0]), "f"(e ? f[2 * r][3] : f[2 * r][2]),
                       "f"(e ? f[2 * r + 1][1] : f[2 * r + 1][0]), "f"(e ? f[2 * r + 1][3] : f[2 * r + 1][2]), "r"(far + r * step + (OFF_BAR + 8 * B_ACT)) : "memory");
    }
    __syncwarp();
    if (warp == 0) {
      sts1(sb + OFF_KEY + 80, ~wtok);
      if (b < 80) bar_arrive<NB_WIN, 64>();
    }
  }
  {
    const uint32_t n0 = __shfl_sync(0xFFFFFFFFu, nw, 2 * gq), n1 = __shfl_sync(0xFFFFFFFFu, nw, 2 * gq + 16);
    nrm[0] = dup_hi(n0); nrm[1] = dup_hi(n1); nrm[2] = dup_lo(n0); nrm[3] = dup_lo(n1);
#pragma unroll
    for (int k = 0; k < 20; ++k) {
      uint32_t& x = xr[k >> 2][k & 3];
      acc2(x, gb[k >> 1], fma2(fma2(x, nrm[k & 1], nrm[2 + (k & 1)]), c1[k >> 1], sv[k >> 1]));
    }
  }
#pragma unroll
  for (int s5 = 0; s5 < 5; ++s5) stsm4(xt + trow * 160 + (OFF_OUT + 32 * s5), xr[s5]);
  asm volatile("fence.proxy.async.shared::cta;" ::: "memory");
  asm volatile("bar.arrive %0, 160;" ::"r"(turn + (NB_OUT - NB_TURN)) : "memory");
  if (p == 1 && b < N_FFN) {
    const uint32_t kr = ((lane & 7) >> 1) + 4 * (lane >> 4) + 8 * (lane & 1);
    uint32_t wd[10][4];
    mbar_wait(bar + 8 * B_XS, 0);
#pragma unroll
    for (int i = 0; i < 10; ++i) ldsm4t(wd[i], sb + OFF_FFN + 40960 + kr * 128 + (((2 * wq + ((lane >> 3) & 1)) ^ (kr & 7)) << 4) + 2048 * i);
    uint4* const ydst = at<16>(P.sc + M_YP, ((b & ~3) + wq) * BOX + 4 * (gq & 6) + 2 * (b & 3) + (gq & 1));
    mbar_wait(bar + 8 * B_ACT, 1);
    float v[8];
#pragma unroll
    for (int i = 0; i < 8; ++i) v[i] = f32(lds1(sb + OFF_ACT + 128 * i + 4 * lane));
    const float gu = bf_round(((v[0] + v[1]) + (v[2] + v[3])) + ((v[4] + v[5]) + (v[6] + v[7])));
    const float a = bf_round(gu * sigmoid(gu)) * shx(gu, 1);
    const uint32_t aw = pack2(a, shx(a, 2));
    const uint32_t b0 = __shfl_sync(0xFFFFFFFFu, aw, 4 * t), b1 = __shfl_sync(0xFFFFFFFFu, aw, 4 * t + 16);
    const bool odd = gq & 1;
    float y[5][4];
#pragma unroll
    for (int q = 0; q < 5; ++q) mma16(y[q], wd[2 * q], odd ? 0u : b0, odd ? 0u : b1, z4);
#pragma unroll
    for (int q = 0; q < 5; ++q) mma16(y[q], wd[2 * q + 1], odd ? b0 : 0u, odd ? b1 : 0u, y[q]);
    uint32_t w[4];
#pragma unroll
    for (int e = 0; e < 4; ++e) w[e] = u32(t & 2 ? (t & 1 ? y[3][e] : y[2][e]) : (t & 1 ? y[1][e] : y[0][e]));
    st_rlx4(ydst + 32 * t, tag(w[0], ep), w[1], w[2], w[3]);
    if (t == 0) st_rlx4(ydst + 128, tag(u32(y[4][0]), ep), u32(y[4][1]), u32(y[4][2]), u32(y[4][3]));
    __syncwarp();
    if (warp == 4 && b < 80) bar_arrive<NB_YP, 64>();
  }
}

template <bool BY_SM>
__global__ void __cluster_dims__(2, 1, 1) __launch_bounds__(384, 1) fused_block_kernel(const __grid_constant__ Params P) {
  extern __shared__ __align__(1024) uint8_t sm[];
  const uint32_t sb = (uint32_t)__cvta_generic_to_shared(sm), t0 = clock32();
  const int tid = threadIdx.x, lane = tid & 31;
  uint32_t key = blockIdx.x;
  if (BY_SM) asm("mov.u32 %0, %%smid;" : "=r"(key));
  const __nv_bfloat16* wmod = (&P.wmod)[tid >> 9];
  asm volatile("" : "+l"(wmod));
  const int warp = __shfl_sync(0xFFFFFFFFu, tid >> 5, 0), c = key >> 1, rank = blockIdx.x & 1;
  const uint32_t bar = sb + OFF_BAR;
  const auto role = [&]() {
    const int q7 = ((c - (BY_SM ? 32 : 36)) * 37) >> 8;
    if (BY_SM) return 2 * pick(c < 32, 8 * (c & 7) + (c >> 3), pick(c < 60, 8 * c - 55 * q7 - 244, c - 58)) + rank;
    return 2 * pick(c < 4, c, pick(c < 36, 4 + 4 * ((c - 4) & 7) + ((c - 4) >> 3), 4 * c - 27 * q7 - 108)) + rank;
  };
  const bool spare = BY_SM && (c >> 1) == 30;
  int budget = SPIN_LIMIT, b;
  uint32_t e0 = 0;
  if (warp == 11) {
    if (elect_one()) {
#pragma unroll
      for (int i = 0; i < 12; ++i) mbar_init(bar + 8 * i, i == B_TAB ? 96 : i == B_HALO ? 8 : (i >> 2) == 1 ? 16 : 1);
      asm volatile("fence.mbarrier_init.release.cluster;" ::: "memory");
    }
    __syncwarp();
    asm volatile("barrier.cluster.arrive.relaxed.aligned;" ::: "memory");
    b = role();
    if (spare) {
      wait_until(t0 + 4000);
      return;
    }
    const int g = (b >> 1) & 7;
    if (elect_one()) {
      mbar_expect_tx(bar + 8 * B_FULL, STAGE);
      tma2(sb, &P.xa, bar + 8 * B_FULL, 640 * rank, 128 * (b >> 4));
    }
    asm volatile("barrier.cluster.wait.aligned;" ::: "memory");
    if (elect_one()) {
      tma3_both(sb + STAGE_A + rank * (STAGE_B0 / 2), &P.w0, bar + 8 * B_FULL, 80 * g + 16 * (g & 1), 32 * rank, 0);
      tma3_both(sb + STAGE_A + STAGE_B0 + rank * (STAGE_B1 / 2), &P.w1, bar + 8 * B_FULL, 80 * g + 64 * (~g & 1), 32 * rank, 0);
    }
    st_rlx1(at<4>(P.sc + M_ST1, b * (4 * BOX) + lane), 0u);
    __syncwarp();
    if (lane == 0) mbar_arrive(bar + 8 * B_XS);
  } else {
    asm volatile("barrier.cluster.arrive.relaxed.aligned;" ::: "memory");
    const int u = (c & 48) + 2 * (c & 7) + ((c >> 3) & 1) - (c & 32 ? c & 7 : 0), kb = 2 * u + rank;
    const bool gemv = warp < 10 && c < 40;
    uint32_t cv = 0;
    if (gemv) {
      const __nv_bfloat16* src = at<16>(wmod, (320 * rank + (tid >> 2)) * 480 + 4 * u + (tid & 3));
      const uint32_t dst = sb + 3 * STAGE + 16 * (tid ^ ((tid >> 3) & 3));
#pragma unroll
      for (int i = 0; i < 4; ++i)
        asm volatile("cp.async.cg.shared.global.L2::128B [%0], [%1], 16;" ::"r"(dst + 5120 * i), "l"(src + i * 80 * 3840) : "memory");
    } else if (warp == 10 && elect_one()) {
      asm volatile("prefetch.tensormap [%0];" ::"l"(&P.xa) : "memory");
      asm volatile("prefetch.tensormap [%0];" ::"l"(&P.w0) : "memory");
      asm volatile("prefetch.tensormap [%0];" ::"l"(&P.w1) : "memory");
    }
    asm volatile("barrier.cluster.wait.aligned;" ::: "memory");
    if (spare) return;
    if (gemv) asm volatile("ld.global.nc.u16 %0, [%1];" : "=r"(cv) : "l"(at<2>(P.c, 320 * rank + 10 * (tid & 24) + ((tid >> 2) & ~7) + (tid & 7))));
    b = role();
    uint4* const box = P.sc + b * BOX;
    e0 = ld_rlx1(at<4>(box + M_EPOCH, lane));
    asm volatile("cp.async.commit_group;" ::: "memory");
    if (warp < 8) {
      const __nv_bfloat16* src = at<16>(P.x, (16 * b + (tid >> 4)) * 80 + (tid & 15));
      wait_until(t0 + XS_AT);
#pragma unroll
      for (int i = 0; i < 5; ++i)
        asm volatile("cp.async.cg.shared.global [%0], [%1], 16;" ::"r"(sb + OFF_XS + 4096 * i + 16 * tid), "l"(src + 128 * i) : "memory");
    }
    if (warp == 10) {
      uint4* const dst = at<16>(P.sc + TABLES, 80 * (lane & 28) + 4 * kb + (lane & 3));
      if (c < 40) st_rlx4(dst, 0u, 0u, 0u, 0u);
      if (lane == 0) mbar_expect_tx(bar + 8 * B_GO, c < 40 ? 1280 : 0);
      if (c < 40) {
        const uint32_t ep = next_epoch(e0);
        mbar_wait(bar + 8 * B_GO, 0);
        float v[10];
#pragma unroll
        for (int i = 0; i < 10; ++i) v[i] = f32(lds1(sb + OFF_RED + 128 * i + 4 * lane));
        float s = ((v[0] + v[1]) + (v[2] + v[3])) + ((v[4] + v[5]) + (v[6] + v[7])) + (v[8] + v[9]);
        s += shx(s, 16);
        const uint32_t w = fma2(pack2(s, shx(s, 1)), 0x3F803F80u, kb < 40 ? 0u : 0x3F803F80u);
        st_rlx4(dst, __shfl_sync(0xFFFFFFFFu, w, 2 * (lane & 3)), __shfl_sync(0xFFFFFFFFu, w, 2 * (lane & 3) + 8), ep, ep);
      }
    } else if (gemv) {
      const float x = bf_lo(cv), s = x * sigmoid(x);
      const uint32_t sw = pack2(s, shx(s, 1));
      uint32_t bw[4], a[4][4];
#pragma unroll
      for (int i = 0; i < 4; ++i) bw[i] = __shfl_sync(0xFFFFFFFFu, sw, 8 * i + 2 * (lane & 3));
      const uint32_t far = map_to_cta(sb, (lane >> 1) & 1), dst = far + OFF_RED + 128 * warp + 64 * rank + 32 * (lane & 1) + (lane & 28);
      const uint32_t la = sb + 3 * STAGE + 512 * warp + (lane >> 4) * 5120 + (lane & 7) * 64 + ((((lane >> 3) & 1) ^ ((lane >> 1) & 3)) << 4);
      sched_fence(P.zero);
      asm volatile("cp.async.wait_group 0;" ::: "memory");
      __syncwarp();
#pragma unroll
      for (int i = 0; i < 4; ++i) ldsm4t(a[i], (la ^ (32 * (i & 1))) + (i >> 1) * 10240);
      float d[2][4];
      const float z4[4] = {0.f, 0.f, 0.f, 0.f};
#pragma unroll
      for (int i = 0; i < 4; ++i) mma16(d[i & 1], a[i], bw[i & 2], bw[(i & 2) + 1], i < 2 ? z4 : d[i & 1]);
      const float v = lane & 2 ? (lane & 1 ? d[1][2] : d[1][0]) : (lane & 1 ? d[0][2] : d[0][0]);
      asm volatile("st.async.weak.shared::cluster.mbarrier::complete_tx::bytes.f32 [%0], %1, [%2];" ::"r"(dst), "f"(v), "r"(far + OFF_BAR + 8 * B_GO) : "memory");
    }
  }
  if (warp >= 8) {
    asm volatile("setmaxnreg.dec.sync.aligned.u32 56;");
    if (warp == 11) {
      wait_until(t0 + S_GAP);
      run_producer(P, sm, sb, b, t0);
    } else {
      run_helper(P, sm, sb, b, warp - 8, next_epoch(e0), budget, t0 + POLL_AT);
    }
  } else {
    run_consumer(P, sm, sb, b, warp, next_epoch(e0), budget);
  }
}

typedef CUresult (*EncodeFn)(CUtensorMap*, CUtensorMapDataType, cuuint32_t, void*, const cuuint64_t*, const cuuint64_t*, const cuuint32_t*,
                             const cuuint32_t*, CUtensorMapInterleave, CUtensorMapSwizzle, CUtensorMapL2promotion, CUtensorMapFloatOOBfill);

void encode(EncodeFn fn, CUtensorMap* m, const void* base, int rank, const cuuint64_t* dims, const cuuint64_t* strides, const cuuint32_t* box,
            CUtensorMapSwizzle sw) {
  const cuuint32_t es[3] = {1, 1, 1};
  fn(m, CU_TENSOR_MAP_DATA_TYPE_BFLOAT16, rank, const_cast<void*>(base), dims, strides, box, es, CU_TENSOR_MAP_INTERLEAVE_NONE, sw,
     CU_TENSOR_MAP_L2_PROMOTION_L2_128B, CU_TENSOR_MAP_FLOAT_OOB_FILL_NONE);
}

}

extern "C" void kernel_launch(void* const* d_in, const int* in_sizes, int n_in, void* d_out, int out_size) {
  (void)in_sizes; (void)n_in; (void)out_size;
  static EncodeFn fn = nullptr;
  static void* scratch = nullptr;
  static bool by_sm = false;
  if (!fn) {
    void* f = nullptr;
    cudaDriverEntryPointQueryResult q;
    cudaGetDriverEntryPoint("cuTensorMapEncodeTiled", &f, cudaEnableDefault, &q);
    fn = (EncodeFn)f;
    cudaFuncSetAttribute(fused_block_kernel<true>, cudaFuncAttributeMaxDynamicSharedMemorySize, SMEM_BYTES);
    cudaFuncSetAttribute(fused_block_kernel<false>, cudaFuncAttributeMaxDynamicSharedMemorySize, SMEM_BYTES);
    int dev = 0, sms = 0, pairs = 0;
    cudaGetDevice(&dev);
    cudaDeviceGetAttribute(&sms, cudaDevAttrMultiProcessorCount, dev);
    cudaLaunchConfig_t cfg = {};
    cudaLaunchAttribute at;
    at.id = cudaLaunchAttributeClusterDimension;
    at.val.clusterDim.x = 2;
    at.val.clusterDim.y = at.val.clusterDim.z = 1;
    cfg.gridDim = dim3(132);
    cfg.blockDim = dim3(384);
    cfg.dynamicSmemBytes = SMEM_BYTES;
    cfg.attrs = &at;
    cfg.numAttrs = 1;
    cudaOccupancyMaxActiveClusters(&pairs, fused_block_kernel<true>, &cfg);
    by_sm = sms == 132 && pairs == 66;
    cudaGetSymbolAddress(&scratch, g_scratch);
  }
  Params P;
  P.sc = (uint4*)scratch;
  P.zero = 0;
  const cuuint64_t xd[2] = {1280, 1024}, xs[1] = {2560};
  const cuuint32_t xb[2] = {64, 128};
  encode(fn, &P.xa, d_in[0], 2, xd, xs, xb, CU_TENSOR_MAP_SWIZZLE_128B);
  const cuuint32_t ob[2] = {80, 16};
  encode(fn, &P.om, d_out, 2, xd, xs, ob, CU_TENSOR_MAP_SWIZZLE_NONE);
  const cuuint64_t wd3[3] = {640, 640, 3}, ws3[2] = {3840, 1280};
  const cuuint32_t w0b[3] = {64, 32, 3}, w1b[3] = {16, 32, 3};
  encode(fn, &P.w0, d_in[1], 3, wd3, ws3, w0b, CU_TENSOR_MAP_SWIZZLE_128B);
  encode(fn, &P.w1, d_in[1], 3, wd3, ws3, w1b, CU_TENSOR_MAP_SWIZZLE_32B);
  const cuuint64_t md[2] = {3840, 640}, ms[1] = {7680};
  const cuuint32_t mb0[2] = {64, 160}, mb1[2] = {16, 160};
  encode(fn, &P.wm0, d_in[9], 2, md, ms, mb0, CU_TENSOR_MAP_SWIZZLE_128B);
  encode(fn, &P.wm1, d_in[9], 2, md, ms, mb1, CU_TENSOR_MAP_SWIZZLE_32B);
  const cuuint64_t od3[3] = {608, 640, 2}, os3[2] = {1280, 64}, od2[2] = {640, 640}, os2[1] = {1280};
  const cuuint32_t oab[3] = {32, 80, 2}, obb[2] = {16, 80};
  encode(fn, &P.woa, d_in[2], 3, od3, os3, oab, CU_TENSOR_MAP_SWIZZLE_64B);
  encode(fn, &P.wob, d_in[2], 2, od2, os2, obb, CU_TENSOR_MAP_SWIZZLE_64B);
  const cuuint64_t gd[3] = {1728, 160, 4}, gs[2] = {3456, 160 * 3456}, dd[3] = {64, 1728, 10}, ds[2] = {1280, 128};
  const cuuint32_t gb[3] = {32, 160, 1}, db[3] = {64, 16, 5};
  encode(fn, &P.wg, d_in[5], 3, gd, gs, gb, CU_TENSOR_MAP_SWIZZLE_64B);
  encode(fn, &P.wu, d_in[6], 3, gd, gs, gb, CU_TENSOR_MAP_SWIZZLE_64B);
  encode(fn, &P.wd, d_in[7], 3, dd, ds, db, CU_TENSOR_MAP_SWIZZLE_128B);
  P.x = (const __nv_bfloat16*)d_in[0];
  P.wqkv = (const __nv_bfloat16*)d_in[1];
  P.wr = (const __nv_bfloat16*)d_in[4];
  P.wo = (const __nv_bfloat16*)d_in[2];
  P.wgate = (const __nv_bfloat16*)d_in[5];
  P.wup = (const __nv_bfloat16*)d_in[6];
  P.wdown = (const __nv_bfloat16*)d_in[7];
  P.c = (const __nv_bfloat16*)d_in[8];
  P.wmod = (const __nv_bfloat16*)d_in[9];
  P.out = (__nv_bfloat16*)d_out;
  if (by_sm) fused_block_kernel<true><<<132, 384, SMEM_BYTES>>>(P);
  else fused_block_kernel<false><<<128, 384, SMEM_BYTES>>>(P);
}
```

```cpp
#include <cuda_runtime.h>
#include <cuda.h>
#include <cuda_bf16.h>
#include <stdint.h>

namespace {

constexpr int STAGE_A = 16384, STAGE_B0 = 24576, STAGE_B1 = 6144, STAGE = STAGE_A + STAGE_B0 + STAGE_B1;
constexpr int WO = 15360;
constexpr int OFF_FFN = 4 * WO, OFF_LM = 2 * STAGE, OFF_X2 = 4 * STAGE, OFF_OUT = 0;
constexpr int OFF_H = 4 * STAGE, OFF_L = OFF_H + 9 * 2560, OFF_XS = OFF_H, OFF_RED = OFF_L, OFF_SINK = OFF_L + 10240;
constexpr int OFF_C1 = 225280, OFF_ACT = OFF_C1, OFF_ROWS = OFF_C1 + 1024, OFF_PRM = OFF_C1 + 2560, OFF_SILU = OFF_PRM + 1600;
constexpr int OFF_KEY = OFF_SILU + 320, OFF_BAR = OFF_KEY + 128, SMEM_BYTES = OFF_BAR + 256;
static_assert(OFF_H % 512 == 0, "lane bits of the halo address");
static_assert(SMEM_BYTES <= 232448 && OFF_BAR % 64 == 0, "smem");
enum { R_GA = 0, R_SB = 160, R_C1 = 320, R_GB = 480, R_FIN = 640, R_P = 800 + R_C1, R_ONE = 704 };

enum { B_FULL = 0, B_EMPTY = 4, B_HALO = 8, B_TAB = 9, B_GO = 10, B_XS = 11, B_ACT = B_FULL, B_FFN = B_FULL + 1, B_WO0 = B_FULL + 2, B_WO1 = B_FULL + 3 };
enum { NB_PV = 1, NB_TURN = 2, NB_KEY = 4, NB_REDO = 5, NB_HELP = 6, NB_HALO = 7, NB_PUB = 8, NB_GO = 9, NB_LM = 10, NB_OUT = 11, NB_WIN = 13, NB_YP = 14 };

enum { M_EARLY = 0, M_ST1 = 32, M_EPOCH = 40, M_HALO = 48, M_ST2 = 208, M_CAND = 336, M_LATE = 368, M_YP = 400, M_O = 560, BOX = 1840 };
constexpr int TABLES = 128 * BOX;
__device__ __align__(1024) uint4 g_scratch[TABLES + 8 * 320];

constexpr int N_FFN = 108;
constexpr uint32_t SMEM_BASE = 1024;
constexpr int AHEAD = 1;
constexpr int FFN_EARLY = 0;
constexpr int DOWN_GAP = 1900;
constexpr int NAP = 20;
constexpr int XS_AT = 900;
constexpr int S_GAP = 1300;
constexpr int POLL_AT = 4000;
constexpr int WPF_AT = 3500;
constexpr int LMPF_AT = 4;
constexpr int TOUCH_AT = 1000;
constexpr int TOUCH_GAP = 1100;
constexpr int HALO_GAP = 400;
constexpr int LATE_GAP = 800;
constexpr int FGO_STEP = 4;
constexpr int FFN_GAP = 0;
constexpr int OUT_AT = 400;
constexpr int OUT_GAP = 0;
constexpr int YP_GAP = 250;
constexpr int PASS1 = 6;
constexpr int PASS0 = 2;
constexpr int PASS_AT = 3;
constexpr int SPIN_LIMIT = 1 << 16;

struct Params {
  const __nv_bfloat16 *wmod, *c, *x;
  uint4* sc;
  uint32_t zero;
  const __nv_bfloat16 *wqkv, *wr, *wo, *wgate, *wup, *wdown;
  __nv_bfloat16* out;
  CUtensorMap xa, w0, w1, wm0, wm1, woa, wob, wg, wu, wd, om;
};

__device__ __forceinline__ uint32_t clock32() {
  uint32_t c;
  asm volatile("mov.u32 %0, %%clock;" : "=r"(c));
  return c;
}

__device__ __forceinline__ void mbar_init(uint32_t b, uint32_t c) { asm volatile("mbarrier.init.shared::cta.b64 [%0], %1;" ::"r"(b), "r"(c) : "memory"); }
__device__ __forceinline__ void mbar_expect_tx(uint32_t b, uint32_t n) { asm volatile("mbarrier.arrive.expect_tx.shared::cta.b64 _, [%0], %1;" ::"r"(b), "r"(n) : "memory"); }
__device__ __forceinline__ void mbar_arrive(uint32_t b) { asm volatile("mbarrier.arrive.shared::cta.b64 _, [%0];" ::"r"(b) : "memory"); }
__device__ __forceinline__ uint32_t map_to_cta(uint32_t a, uint32_t rank) {
  uint32_t r;
  asm("mapa.shared::cluster.u32 %0, %1, %2;" : "=r"(r) : "r"(a), "r"(rank));
  return r;
}
__device__ __forceinline__ void mbar_arrive_cluster(uint32_t b) { asm volatile("mbarrier.arrive.shared::cluster.b64 _, [%0];" ::"r"(b) : "memory"); }
__device__ __forceinline__ void mbar_wait(uint32_t b, uint32_t ph) {
  asm volatile("{.reg .pred p;\n"
               "RETRY: mbarrier.try_wait.parity.shared::cta.b64 p, [%0], %1;\n"
               "@!p bra RETRY;}" ::"r"(b), "r"(ph) : "memory");
}
__device__ __forceinline__ bool elect_one() {
  uint32_t r;
  asm volatile("{.reg .pred p; elect.sync _|p, 0xFFFFFFFF; selp.u32 %0, 1, 0, p;}" : "=r"(r));
  return r;
}
template <int ID, int N> __device__ __forceinline__ void bar_sync() { asm volatile("bar.sync %0, %1;" ::"n"(ID), "n"(N) : "memory"); }
template <int ID, int N> __device__ __forceinline__ void bar_arrive() { asm volatile("bar.arrive %0, %1;" ::"n"(ID), "n"(N) : "memory"); }
__device__ __forceinline__ void turn_wait(uint32_t id) { asm volatile("bar.sync %0, 256;" ::"r"(id) : "memory"); }
__device__ __forceinline__ void turn_pass(uint32_t id) { asm volatile("bar.arrive %0, 256;" ::"r"(id) : "memory"); }
__device__ __forceinline__ void tma2(uint32_t dst, const CUtensorMap* m, uint32_t bar, int c0, int c1) {
  asm volatile("cp.async.bulk.tensor.2d.shared::cluster.global.mbarrier::complete_tx::bytes [%0], [%1, {%3, %4}], [%2];" ::"r"(dst), "l"(m), "r"(bar), "r"(c0), "r"(c1) : "memory");
}
__device__ __forceinline__ void tma3(uint32_t dst, const CUtensorMap* m, uint32_t bar, int c0, int c1, int c2) {
  asm volatile("cp.async.bulk.tensor.3d.shared::cluster.global.mbarrier::complete_tx::bytes [%0], [%1, {%3, %4, %5}], [%2];" ::"r"(dst), "l"(m), "r"(bar), "r"(c0), "r"(c1), "r"(c2) : "memory");
}
__device__ __forceinline__ void tma2_both(uint32_t dst, const CUtensorMap* m, uint32_t bar, int c0, int c1) {
  asm volatile("cp.async.bulk.tensor.2d.shared::cluster.global.mbarrier::complete_tx::bytes.multicast::cluster [%0], [%1, {%3, %4}], [%2], %5;"
               ::"r"(dst), "l"(m), "r"(bar), "r"(c0), "r"(c1), "h"((uint16_t)3) : "memory");
}
__device__ __forceinline__ void tma3_both(uint32_t dst, const CUtensorMap* m, uint32_t bar, int c0, int c1, int c2) {
  asm volatile("cp.async.bulk.tensor.3d.shared::cluster.global.mbarrier::complete_tx::bytes.multicast::cluster [%0], [%1, {%3, %4, %5}], [%2], %6;"
               ::"r"(dst), "l"(m), "r"(bar), "r"(c0), "r"(c1), "r"(c2), "h"((uint16_t)3) : "memory");
}
__device__ __forceinline__ void bulk_prefetch(const void* src, uint32_t bytes) {
  asm volatile("cp.async.bulk.prefetch.L2.global [%0], %1;" ::"l"(src), "r"(bytes) : "memory");
}
__device__ __forceinline__ void wg_fence() { asm volatile("wgmma.fence.sync.aligned;" ::: "memory"); }
__device__ __forceinline__ void wg_commit() { asm volatile("wgmma.commit_group.sync.aligned;" ::: "memory"); }
__device__ __forceinline__ void wg_wait() { asm volatile("wgmma.wait_group.sync.aligned 0;" ::: "memory"); }
__device__ __forceinline__ constexpr uint64_t make_desc(uint32_t addr, uint32_t lbo, uint32_t sbo, uint32_t mode) {
  return (uint64_t)((addr & 0x3FFFF) >> 4) | ((uint64_t)(lbo >> 4) << 16) | ((uint64_t)(sbo >> 4) << 32) | ((uint64_t)mode << 62);
}
__device__ __forceinline__ void ldsm4(uint32_t& r0, uint32_t& r1, uint32_t& r2, uint32_t& r3, uint32_t a) {
  asm volatile("ldmatrix.sync.aligned.m8n8.x4.shared.b16 {%0, %1, %2, %3}, [%4];" : "=r"(r0), "=r"(r1), "=r"(r2), "=r"(r3) : "r"(a) : "memory");
}
__device__ __forceinline__ void ldsm4(uint32_t* r, uint32_t a) { ldsm4(r[0], r[1], r[2], r[3], a); }
__device__ __forceinline__ void ldsm2(uint32_t* r, uint32_t a) {
  asm volatile("ldmatrix.sync.aligned.m8n8.x2.shared.b16 {%0, %1}, [%2];" : "=r"(r[0]), "=r"(r[1]) : "r"(a) : "memory");
}
__device__ __forceinline__ void ldsm4t(uint32_t* r, uint32_t a) {
  asm volatile("ldmatrix.sync.aligned.m8n8.x4.trans.shared.b16 {%0, %1, %2, %3}, [%4];" : "=r"(r[0]), "=r"(r[1]), "=r"(r[2]), "=r"(r[3]) : "r"(a) : "memory");
}
__device__ __forceinline__ void ldsm2t(uint32_t* r, uint32_t a) {
  asm volatile("ldmatrix.sync.aligned.m8n8.x2.trans.shared.b16 {%0, %1}, [%2];" : "=r"(r[0]), "=r"(r[1]) : "r"(a) : "memory");
}
__device__ __forceinline__ void ld_row(uint32_t (&r)[10], uint32_t a) {
  ldsm4(r, a);
  ldsm4(r + 4, a + 64);
  ldsm2(r + 8, a + 128);
}
__device__ __forceinline__ void stsm4(uint32_t a, const uint32_t* r) {
  asm volatile("stmatrix.sync.aligned.m8n8.x4.shared.b16 [%0], {%1, %2, %3, %4};" ::"r"(a), "r"(r[0]), "r"(r[1]), "r"(r[2]), "r"(r[3]) : "memory");
}
__device__ __forceinline__ void stsm2(uint32_t a, const uint32_t* r) {
  asm volatile("stmatrix.sync.aligned.m8n8.x2.shared.b16 [%0], {%1, %2};" ::"r"(a), "r"(r[0]), "r"(r[1]) : "memory");
}
__device__ __forceinline__ void lds4(uint32_t* r, uint32_t a) {
  asm volatile("ld.shared.v4.u32 {%0, %1, %2, %3}, [%4];" : "=r"(r[0]), "=r"(r[1]), "=r"(r[2]), "=r"(r[3]) : "r"(a) : "memory");
}
__device__ __forceinline__ uint32_t lds1(uint32_t a) {
  uint32_t v;
  asm volatile("ld.shared.u32 %0, [%1];" : "=r"(v) : "r"(a) : "memory");
  return v;
}
__device__ __forceinline__ void sts1(uint32_t a, uint32_t v) { asm volatile("st.shared.u32 [%0], %1;" ::"r"(a), "r"(v) : "memory"); }
__device__ __forceinline__ void sts2(uint32_t a, uint32_t v0, uint32_t v1) { asm volatile("st.shared.v2.u32 [%0], {%1, %2};" ::"r"(a), "r"(v0), "r"(v1) : "memory"); }
__device__ __forceinline__ void mma16(float (&d)[4], uint32_t a0, uint32_t a1, uint32_t a2, uint32_t a3, uint32_t b0, uint32_t b1, const float* c) {
  asm volatile("mma.sync.aligned.m16n8k16.row.col.f32.bf16.bf16.f32 {%0, %1, %2, %3}, {%4, %5, %6, %7}, {%8, %9}, {%10, %11, %12, %13};"
               : "=f"(d[0]), "=f"(d[1]), "=f"(d[2]), "=f"(d[3])
               : "r"(a0), "r"(a1), "r"(a2), "r"(a3), "r"(b0), "r"(b1), "f"(c[0]), "f"(c[1]), "f"(c[2]), "f"(c[3]));
}
__device__ __forceinline__ void mma16(float (&d)[4], const uint32_t* a, uint32_t b0, uint32_t b1, const float* c) { mma16(d, a[0], a[1], a[2], a[3], b0, b1, c); }
__device__ __forceinline__ void mma8(float (&d)[4], uint32_t a0, uint32_t a1, uint32_t b0, const float* c) {
  asm volatile("mma.sync.aligned.m16n8k8.row.col.f32.bf16.bf16.f32 {%0, %1, %2, %3}, {%4, %5}, {%6}, {%7, %8, %9, %10};"
               : "=f"(d[0]), "=f"(d[1]), "=f"(d[2]), "=f"(d[3]) : "r"(a0), "r"(a1), "r"(b0), "f"(c[0]), "f"(c[1]), "f"(c[2]), "f"(c[3]));
}
__device__ __forceinline__ uint32_t pack2(float lo, float hi) {
  uint32_t r;
  asm volatile("cvt.rn.bf16x2.f32 %0, %1, %2;" : "=r"(r) : "f"(hi), "f"(lo));
  return r;
}
__device__ __forceinline__ float bf_lo(uint32_t w) { return __uint_as_float(w << 16); }
__device__ __forceinline__ float bf_hi(uint32_t w) { return __uint_as_float(w & 0xFFFF0000u); }
__device__ __forceinline__ float bf_round(float v) { return __uint_as_float(pack2(0.f, v)); }
__device__ __forceinline__ uint32_t fma2(uint32_t a, uint32_t b, uint32_t c) {
  uint32_t r;
  asm("fma.rn.bf16x2 %0, %1, %2, %3;" : "=r"(r) : "r"(a), "r"(b), "r"(c));
  return r;
}
__device__ __forceinline__ void acc2(uint32_t& c, uint32_t a, uint32_t b) { asm("fma.rn.bf16x2 %0, %1, %2, %0;" : "+r"(c) : "r"(a), "r"(b)); }
__device__ __forceinline__ float ex2(float v) {
  float r;
  asm("ex2.approx.ftz.f32 %0, %1;" : "=f"(r) : "f"(v));
  return r;
}
__device__ __forceinline__ float rcp(float v) {
  float r;
  asm("rcp.approx.ftz.f32 %0, %1;" : "=f"(r) : "f"(v));
  return r;
}
__device__ __forceinline__ float rsq(float v) {
  float r;
  asm("rsqrt.approx.ftz.f32 %0, %1;" : "=f"(r) : "f"(v));
  return r;
}
__device__ __forceinline__ float sigmoid(float v) { return rcp(1.f + ex2(v * -1.4426950408889634f)); }
__device__ __forceinline__ float f32(uint32_t v) { return __uint_as_float(v); }
__device__ __forceinline__ uint32_t u32(float v) { return __float_as_uint(v); }
__device__ __forceinline__ void ld_rlx4(uint32_t* v, const void* p) {
  asm volatile("{.reg .b128 q; ld.relaxed.gpu.global.b128 q, [%4]; mov.b128 {%0, %1, %2, %3}, q;}" : "=r"(v[0]), "=r"(v[1]), "=r"(v[2]), "=r"(v[3]) : "l"(p) : "memory");
}
__device__ __forceinline__ void ld_rlx2(uint32_t* v, const void* p) {
  asm volatile("{.reg .b64 q; ld.relaxed.gpu.global.b64 q, [%2]; mov.b64 {%0, %1}, q;}" : "=r"(v[0]), "=r"(v[1]) : "l"(p) : "memory");
}
__device__ __forceinline__ uint32_t ld_rlx1(const void* p) {
  uint32_t v;
  asm volatile("ld.relaxed.gpu.global.u32 %0, [%1];" : "=r"(v) : "l"(p) : "memory");
  return v;
}
__device__ __forceinline__ void st_rlx4(void* p, uint32_t a, uint32_t b, uint32_t c, uint32_t d) {
  asm volatile("{.reg .b128 q; mov.b128 q, {%1, %2, %3, %4}; st.relaxed.gpu.global.b128 [%0], q;}" ::"l"(p), "r"(a), "r"(b), "r"(c), "r"(d) : "memory");
}
__device__ __forceinline__ void st_rlx4(void* p, const uint32_t* v) { st_rlx4(p, v[0], v[1], v[2], v[3]); }
__device__ __forceinline__ void st_rlx2(void* p, uint32_t a, uint32_t b) { asm volatile("{.reg .b64 q; mov.b64 q, {%1, %2}; st.relaxed.gpu.global.b64 [%0], q;}" ::"l"(p), "r"(a), "r"(b) : "memory"); }
__device__ __forceinline__ void st_rlx1(void* p, uint32_t v) { asm volatile("st.relaxed.gpu.global.u32 [%0], %1;" ::"l"(p), "r"(v) : "memory"); }
template <int LUT> __device__ __forceinline__ uint32_t lop3(uint32_t a, uint32_t b, uint32_t c) {
  uint32_t r;
  asm volatile("lop3.b32 %0, %1, %2, %3, %4;" : "=r"(r) : "r"(a), "r"(b), "r"(c), "n"(LUT));
  return r;
}
__device__ __forceinline__ uint32_t tag(uint32_t w, uint32_t ep) { return lop3<0xD8>(w, ep, 1u); }
__device__ __forceinline__ uint32_t neq2(uint32_t a, uint32_t b, uint32_t e) { return lop3<0x7E>(a, b, e); }
__device__ __forceinline__ uint32_t next_epoch(uint32_t e) {
  asm volatile("add.u32 %0, %0, 1;" : "+r"(e));
  return e;
}
__device__ __forceinline__ void sched_fence(uint32_t zero) {
  asm volatile("{.reg .pred p; setp.ne.u32 p, %0, 0;\nSPIN: pmevent 0; @p bra.uni SPIN;}" ::"r"(zero) : "memory");
}
__device__ __forceinline__ int pick(bool c, int a, int b) {
  int r;
  asm("{.reg .pred p; setp.ne.u32 p, %1, 0; selp.b32 %0, %2, %3, p;}" : "=r"(r) : "r"((uint32_t)c), "r"(a), "r"(b));
  return r;
}
__device__ __forceinline__ uint32_t keep(uint32_t v) { return __shfl_xor_sync(0xFFFFFFFFu, v, 2); }
__device__ __forceinline__ void wait_until(uint32_t t) {
  while ((int)(clock32() - t) < 0) {
    asm volatile("nanosleep.u32 %0;" ::"n"(NAP));
  }
}
__device__ __forceinline__ float shx(float v, int o) { return __shfl_xor_sync(0xFFFFFFFFu, v, o); }
template <int SCALE, class T> __device__ __forceinline__ T* at(T* base, uint32_t i) {
  T* r;
  asm volatile("mad.wide.u32 %0, %1, %2, %3;" : "=l"(r) : "r"(i), "n"(SCALE), "l"(base));
  return r;
}
template <uint32_t MASK> __device__ __forceinline__ bool retry(uint32_t bad, int& budget) {
  uint32_t r;
  asm volatile("{.reg .pred p, q; .reg .b32 t; add.s32 %1, %1, -1; setp.gt.s32 q, %1, 0; and.b32 t, %2, %3; setp.ne.u32 p, t, 0;\n"
               "vote.sync.any.pred p, p, 0xFFFFFFFF; and.pred p, p, q; selp.u32 %0, 1, 0, p;}" : "=r"(r), "+r"(budget) : "r"(bad), "n"(MASK));
  return r;
}
template <int N, int W> __device__ __forceinline__ uint32_t stale(const uint32_t (*v)[4], uint32_t ep) {
  uint32_t bad = neq2(v[0][W], v[N > 1][W], ep);
#pragma unroll
  for (int i = 2; i < N; i += 2) bad |= neq2(v[i][W], v[i + 1 < N ? i + 1 : i][W], ep);
  return bad;
}
__device__ __forceinline__ void ld_rlx4_stale(uint32_t* v, const void* p, uint32_t w, uint32_t ep) {
  asm volatile("{.reg .b128 q; .reg .pred p; .reg .b32 t; lop3.b32 t, %5, %6, 1, 0x28; setp.ne.u32 p, t, 0; mov.b128 q, {%0, %1, %2, %3};\n"
               "@p ld.relaxed.gpu.global.b128 q, [%4]; mov.b128 {%0, %1, %2, %3}, q;}"
               : "+r"(v[0]), "+r"(v[1]), "+r"(v[2]), "+r"(v[3]) : "l"(p), "r"(w), "r"(ep) : "memory");
}
template <int N, int S0, int S1, int W> __device__ __forceinline__ void gather_lazy(uint32_t (*v)[4], const uint4* p, uint32_t ep, int& budget, bool skip_last = false) {
#pragma unroll
  for (int i = 0; i < 4 * N; ++i) {
    if ((i & 3) == W) v[i >> 2][W] = N == 7 && i >= 24 && skip_last ? ep & 1u : ~ep;
    else if (N == 7 && i >= 24) v[6][i & 3] = 0;
    else asm volatile("" : "=r"(v[i >> 2][i & 3]));
  }
#pragma unroll 1
  do {
#pragma unroll
    for (int i = 0; i < N; ++i) ld_rlx4_stale(v[i], p + (i & 1) * S0 + (i >> 1) * S1, v[i][W], ep);
  } while (retry<1>(stale<N, W>(v, ep), budget));
}
template <int N, int STRIDE, int W> __device__ __forceinline__ void gather(uint32_t (*v)[4], const uint4* p, uint32_t ep, int& budget) {
#pragma unroll 1
  do {
#pragma unroll
    for (int i = 0; i < N; ++i) ld_rlx4(v[i], p + i * STRIDE);
  } while (retry<1>(stale<N, W>(v, ep), budget));
}
__device__ __forceinline__ void row_stats(float (&s)[4], float& qlo, float& qhi, const uint32_t (&x)[5][4], const uint32_t (&b)[10], int gq) {
  const float z[4] = {0.f, 0.f, 0.f, 0.f};
  float q[4][4];
#pragma unroll
  for (int i = 0; i < 5; ++i) {
    mma16(s, x[i], b[2 * i], b[2 * i + 1], i ? s : z);
#pragma unroll
    for (int e = 0; e < 4; ++e) mma8(q[e], x[i][e & 2], x[i][(e & 2) + 1], x[i][e], i ? q[e] : z);
  }
  const bool odd = gq & 1;
  qlo = (odd ? q[0][1] : q[0][0]) + (odd ? q[2][1] : q[2][0]);
  qhi = (odd ? q[1][3] : q[1][2]) + (odd ? q[3][3] : q[3][2]);
}
__device__ __forceinline__ uint32_t norm_word(float s, float q, float& mean, float& rstd) {
  mean = s * (1.f / 640.f);
  rstd = rsq(fmaxf(fmaf(q, 1.f / 640.f, -mean * mean), 0.f) + 1e-5f);
  return pack2(-mean * bf_round(rstd), rstd);
}
__device__ __forceinline__ uint32_t dup_lo(uint32_t w) { return __byte_perm(w, 0u, 0x1010); }
__device__ __forceinline__ uint32_t dup_hi(uint32_t w) { return __byte_perm(w, 0u, 0x3232); }

__device__ __forceinline__ void wgmma_n192(float (&d)[96], const uint32_t (&a)[4], uint64_t db, int add) {
  asm volatile("{.reg .pred p; setp.ne.b32 p, %101, 0; wgmma.mma_async.sync.aligned.m64n192k16.f32.bf16.bf16 "
    "{%0, %1, %2, %3, %4, %5, %6, %7, %8, %9, %10, %11, %12, %13, %14, %15, "
    "%16, %17, %18, %19, %20, %21, %22, %23, %24, %25, %26, %27, %28, %29, %30, %31, "
    "%32, %33, %34, %35, %36, %37, %38, %39, %40, %41, %42, %43, %44, %45, %46, %47, "
    "%48, %49, %50, %51, %52, %53, %54, %55, %56, %57, %58, %59, %60, %61, %62, %63, "
    "%64, %65, %66, %67, %68, %69, %70, %71, %72, %73, %74, %75, %76, %77, %78, %79, "
    "%80, %81, %82, %83, %84, %85, %86, %87, %88, %89, %90, %91, %92, %93, %94, %95}, "
    "{%96, %97, %98, %99}, %100, p, 1, 1, 1;}"
    : "+f"(d[0]), "+f"(d[1]), "+f"(d[2]), "+f"(d[3]), "+f"(d[4]), "+f"(d[5]), "+f"(d[6]), "+f"(d[7]),
      "+f"(d[8]), "+f"(d[9]), "+f"(d[10]), "+f"(d[11]), "+f"(d[12]), "+f"(d[13]), "+f"(d[14]), "+f"(d[15]),
      "+f"(d[16]), "+f"(d[17]), "+f"(d[18]), "+f"(d[19]), "+f"(d[20]), "+f"(d[21]), "+f"(d[22]), "+f"(d[23]),
      "+f"(d[24]), "+f"(d[25]), "+f"(d[26]), "+f"(d[27]), "+f"(d[28]), "+f"(d[29]), "+f"(d[30]), "+f"(d[31]),
      "+f"(d[32]), "+f"(d[33]), "+f"(d[34]), "+f"(d[35]), "+f"(d[36]), "+f"(d[37]), "+f"(d[38]), "+f"(d[39]),
      "+f"(d[40]), "+f"(d[41]), "+f"(d[42]), "+f"(d[43]), "+f"(d[44]), "+f"(d[45]), "+f"(d[46]), "+f"(d[47]),
      "+f"(d[48]), "+f"(d[49]), "+f"(d[50]), "+f"(d[51]), "+f"(d[52]), "+f"(d[53]), "+f"(d[54]), "+f"(d[55]),
      "+f"(d[56]), "+f"(d[57]), "+f"(d[58]), "+f"(d[59]), "+f"(d[60]), "+f"(d[61]), "+f"(d[62]), "+f"(d[63]),
      "+f"(d[64]), "+f"(d[65]), "+f"(d[66]), "+f"(d[67]), "+f"(d[68]), "+f"(d[69]), "+f"(d[70]), "+f"(d[71]),
      "+f"(d[72]), "+f"(d[73]), "+f"(d[74]), "+f"(d[75]), "+f"(d[76]), "+f"(d[77]), "+f"(d[78]), "+f"(d[79]),
      "+f"(d[80]), "+f"(d[81]), "+f"(d[82]), "+f"(d[83]), "+f"(d[84]), "+f"(d[85]), "+f"(d[86]), "+f"(d[87]),
      "+f"(d[88]), "+f"(d[89]), "+f"(d[90]), "+f"(d[91]), "+f"(d[92]), "+f"(d[93]), "+f"(d[94]), "+f"(d[95])
    : "r"(a[0]), "r"(a[1]), "r"(a[2]), "r"(a[3]), "l"(db), "r"(add));
}
__device__ __forceinline__ void wgmma_n48(float (&d)[24], const uint32_t (&a)[4], uint64_t db, int add) {
  asm volatile("{.reg .pred p; setp.ne.b32 p, %29, 0; wgmma.mma_async.sync.aligned.m64n48k16.f32.bf16.bf16 "
    "{%0, %1, %2, %3, %4, %5, %6, %7, %8, %9, %10, %11, %12, %13, %14, %15, "
    "%16, %17, %18, %19, %20, %21, %22, %23}, "
    "{%24, %25, %26, %27}, %28, p, 1, 1, 1;}"
    : "+f"(d[0]), "+f"(d[1]), "+f"(d[2]), "+f"(d[3]), "+f"(d[4]), "+f"(d[5]), "+f"(d[6]), "+f"(d[7]),
      "+f"(d[8]), "+f"(d[9]), "+f"(d[10]), "+f"(d[11]), "+f"(d[12]), "+f"(d[13]), "+f"(d[14]), "+f"(d[15]),
      "+f"(d[16]), "+f"(d[17]), "+f"(d[18]), "+f"(d[19]), "+f"(d[20]), "+f"(d[21]), "+f"(d[22]), "+f"(d[23])
    : "r"(a[0]), "r"(a[1]), "r"(a[2]), "r"(a[3]), "l"(db), "r"(add));
}
__device__ __forceinline__ void wgmma_n80(float (&d)[40], const uint32_t (&a)[4], uint64_t db, int add) {
  asm volatile("{.reg .pred p; setp.ne.b32 p, %45, 0; wgmma.mma_async.sync.aligned.m64n80k16.f32.bf16.bf16 "
    "{%0, %1, %2, %3, %4, %5, %6, %7, %8, %9, %10, %11, %12, %13, %14, %15, "
    "%16, %17, %18, %19, %20, %21, %22, %23, %24, %25, %26, %27, %28, %29, %30, %31, "
    "%32, %33, %34, %35, %36, %37, %38, %39}, "
    "{%40, %41, %42, %43}, %44, p, 1, 1, 1;}"
    : "+f"(d[0]), "+f"(d[1]), "+f"(d[2]), "+f"(d[3]), "+f"(d[4]), "+f"(d[5]), "+f"(d[6]), "+f"(d[7]),
      "+f"(d[8]), "+f"(d[9]), "+f"(d[10]), "+f"(d[11]), "+f"(d[12]), "+f"(d[13]), "+f"(d[14]), "+f"(d[15]),
      "+f"(d[16]), "+f"(d[17]), "+f"(d[18]), "+f"(d[19]), "+f"(d[20]), "+f"(d[21]), "+f"(d[22]), "+f"(d[23]),
      "+f"(d[24]), "+f"(d[25]), "+f"(d[26]), "+f"(d[27]), "+f"(d[28]), "+f"(d[29]), "+f"(d[30]), "+f"(d[31]),
      "+f"(d[32]), "+f"(d[33]), "+f"(d[34]), "+f"(d[35]), "+f"(d[36]), "+f"(d[37]), "+f"(d[38]), "+f"(d[39])
    : "r"(a[0]), "r"(a[1]), "r"(a[2]), "r"(a[3]), "l"(db), "r"(add));
}

__device__ __forceinline__ constexpr int wo_off(int i) { return (i < 4 ? 8 + i : i - 4) * WO; }
__device__ __forceinline__ void load_stage(const Params& P, uint32_t sb, int st, int j, int g, int rank) {
  const uint32_t fb = sb + OFF_BAR + 8 * (B_FULL + (st & 3)), a = sb + (st & 3) * STAGE;
  mbar_expect_tx(fb, STAGE);
  tma2(a, &P.xa, fb, 640 * rank + 64 * st, 128 * j);
  tma3_both(a + STAGE_A + rank * (STAGE_B0 / 2), &P.w0, fb, 80 * g + 16 * (g & 1), 64 * st + 32 * rank, 0);
  tma3_both(a + STAGE_A + STAGE_B0 + rank * (STAGE_B1 / 2), &P.w1, fb, 80 * g + 64 * (~g & 1), 64 * st + 32 * rank, 0);
}

__device__ __forceinline__ void run_producer(const Params& P, uint8_t* sm, uint32_t sb, int b, uint32_t t0) {
  const int rank = b & 1, g = (b >> 1) & 7, j = b >> 4;
  const uint32_t bar = sb + OFF_BAR;
#pragma unroll 1
  for (int st = 1; st < 10; ++st) {
    if (st == 2) {
      wait_until(t0 + WPF_AT);
      if (elect_one()) bulk_prefetch(P.wqkv + (128 + b) * 1920, 3840);
      bar_sync<NB_GO, 160>();
    }
    if (st == 9) bar_sync<NB_HELP, 128>();
    mbar_wait(bar + 8 * (B_EMPTY + (st & 3)), (((st + 1) >> 2) + 1) & 1);
    if (elect_one()) {
      load_stage(P, sb, st, j, g, rank);
      if (st >= 2 && st < 8) bulk_prefetch(P.wqkv + ((st + 2) * 128 + b) * 960, 1920);
      const int k = st - LMPF_AT;
      if ((uint32_t)k < 5u) bulk_prefetch(P.wmod + (5 * b + k) * 3840 + 1280, 5120);
      if (st == 7) bulk_prefetch(P.wo + b * 3200, 6400);
    }
  }
#pragma unroll 1
  for (int i = 0; i < 8; ++i) {
    if (i < 2 || i == 4 || i == 7) mbar_wait(bar + 8 * (B_EMPTY + (i < 2 ? 2 + i : i & 1)), i == 0);
    if (elect_one()) {
      const uint32_t fb = bar + 8 * (i ? B_WO1 : B_WO0), a = sb + (i < 4 ? 8 + i : i - 4) * WO;
      if (i == 0) {
        mbar_expect_tx(bar + 8 * B_XS, 25600);
        tma2(sb + OFF_LM, &P.wm0, bar + 8 * B_XS, 1280 + 64 * (b & 31), 160 * (b >> 5));
        tma2(sb + OFF_LM + 20480, &P.wm1, bar + 8 * B_XS, 3328 + 16 * (b & 31), 160 * (b >> 5));
      }
      if (i < 2) mbar_expect_tx(fb, i ? 7 * 12800 : 12800);
      if ((i & 1) == rank) {
        const int k0 = 80 * (i ? i - (i <= g) : g);
        tma3_both(a, &P.woa, fb, 80 * g, k0, 0);
        tma2_both(a + 10240, &P.wob, fb, 80 * g + 64, k0);
      }
    }
  }
  if (b < N_FFN) {
    if (elect_one()) {
      mbar_expect_tx(bar + 8 * B_ACT, 1024);
      mbar_expect_tx(bar + 8 * B_FFN, 40960);
    }
    uint32_t next = clock32();
#pragma unroll 1
    for (int i = 0; i < 6; ++i) {
      if (i == FFN_EARLY) {
        mbar_wait(bar + 8 * B_GO, 1);
        next = clock32();
      }
      if (i == 3) bar_sync<NB_LM, 128>();
      if (i == 4) next += DOWN_GAP;
      wait_until(next);
      next += FFN_GAP;
      if (elect_one())
        tma3(sb + OFF_FFN + 10240 * i, &P.wg + (i >> 1), bar + 8 * (i < 4 ? B_FFN : B_XS), i < 4 ? 32 * (b >> 1) : 0, i < 4 ? 0 : 16 * b, i < 4 ? 2 * rank + (i & 1) : 5 * (i & 1));
    }
  }
}

__device__ __forceinline__ void run_helper(const Params& P, uint8_t* sm, uint32_t sb, int b, int hw, uint32_t ep, int budget, uint32_t poll_at) {
  const int h = threadIdx.x - 256, lane = h & 31, gq = lane >> 2, t = lane & 3, rank = b & 1, g = (b >> 1) & 7, j = b >> 4;
  const uint32_t bar = sb + OFF_BAR, prm = sb + OFF_PRM;
  uint4* const box = P.sc + b * BOX;
  const bool main20 = lane < 20;
  const int fin = 128 * (b >> 4) + 16 * ((b >> 2) & 3) + 2 * (b & 3) + (lane & 1) + 32 * (lane & 2) + 2 * (lane & 4);
  const int which = main20 ? 2 - hw : 3, fsl = (fin * 205) >> 14;
  const int q4 = main20 ? lane : min(10 * hw + lane - 20, 19);
  uint32_t wr[2];
  asm volatile("ld.global.nc.v2.u32 {%0, %1}, [%2];" : "=r"(wr[0]), "=r"(wr[1]) : "l"(P.wr + 80 * g + 4 * q4));
  uint32_t cw;
  asm volatile("ld.global.nc.u32 %0, [%1];" : "=r"(cw) : "l"(P.c + 160 * (b >> 5) + 2 * min(h, 79)));
  sts1(sb + OFF_SILU + 4 * min(h, 79), pack2(bf_lo(cw) * sigmoid(bf_lo(cw)), bf_hi(cw) * sigmoid(bf_hi(cw))));
  if (h < 4) sts1(prm + R_ONE + 4 * h, 0x3F803F80u);
  wait_until(poll_at);
  {
    uint32_t v[4][4];
    const int h80 = min(h, 79);
    const uint4* src = at<16>(P.sc + TABLES, 320 * j + h80);
#pragma unroll 1
    do {
#pragma unroll
      for (int i = 0; i < 4; ++i) ld_rlx4(v[i], src + i * 80);
    } while (retry<~0u>(stale<4, 2>(v, ep), budget));
#pragma unroll
    for (int i = 0; i < 4; ++i) sts2(sb + OFF_C1 + 16 * h80 + 1280 * (i & 1) + (i < 2 ? 8 : 0), v[i][0], v[i][1]);
    mbar_arrive(bar + 8 * B_TAB);
  }
  bar_sync<NB_GO, 160>();
  {
    const char* src = hw == 2 ? at<128>(reinterpret_cast<const char*>(P.wdown), 160 * b + lane)
                              : at<128>(reinterpret_cast<const char*>(hw ? P.wup : P.wgate), (160 * (b & 3) + lane) * 27 + (b >> 2));
    uint4* slot = at<16>(box + M_HALO, h);
    uint32_t next = clock32() + TOUCH_AT + hw * (TOUCH_GAP / 3);
#pragma unroll 1
    for (int i = 0; i < 5; ++i) {
      wait_until(next);
      next += TOUCH_GAP;
      if (b < N_FFN) asm volatile("cp.async.cg.shared.global.L2::128B [%0], [%1], 16;" ::"r"(sb + OFF_SINK + 16 * h), "l"(src) : "memory");
      src += hw == 2 ? 4096 : 32 * 3456;
      if (i < 4) {
        st_rlx4(slot, ~ep, ~ep, ~ep, ~ep);
        st_rlx4(slot + 96, ~ep, ~ep, ~ep, ~ep);
      }
      slot += 192;
    }
  }
  bar_sync<NB_HELP, 128>();

  {
    float d0[4] = {0.f, 0.f, 0.f, 0.f}, d1[4] = {0.f, 0.f, 0.f, 0.f};
    const uint32_t row = 8 * (lane >> 4) + (lane & 7), half = (lane >> 3) & 1, kstep = hw < 2 ? 2048 : 512;
    uint32_t wa = sb + OFF_LM + (hw < 2 ? row * 128 + (((4 * hw + half) ^ (lane & 7)) << 4) : 20480 + row * 32 + ((half ^ ((lane >> 2) & 1)) << 4)), sa = sb + OFF_SILU + (lane >> 3) * 16;
    mbar_wait(bar + 8 * B_XS, 1);
    {
      uint32_t hv[2][4] = {};
      const int q = min(2 * hw, 3);
      const uint4* const src = at<16>(box + (M_HALO - 16 * BOX), 32 * q + lane);
      mbar_wait(bar + 8 * B_EMPTY, 0);
      wait_until(clock32() + HALO_GAP);
      if (j > 0) gather<2, 32, 0>(hv, src, ep, budget);
      stsm4(sb + OFF_H + 512 * q + 16 * lane, hv[0]);
      stsm4(sb + OFF_H + 512 * q + 16 * lane + 512, hv[1]);
      bar_arrive<NB_HALO, 128>();
    }
    mbar_wait(bar + 8 * (B_EMPTY + 1), 0);
    const uint32_t o1 = hw < 2 ? (wa ^ 32) - wa : 1024, s1 = hw < 2 ? 0 : 64;
#pragma unroll 1
    for (int u = hw < 2 ? 0 : 2; u < 5; ++u) {
      uint32_t a[4][4], s[2][4];
      ldsm4(s[0], sa);
      ldsm4t(a[0], wa);
      ldsm4t(a[1], wa + o1);
      ldsm4(s[1], sa + s1);
      ldsm4t(a[2], wa + kstep);
      ldsm4t(a[3], wa + kstep + o1);
      sched_fence(P.zero);
      mma16(d0, a[0], s[0][0], s[0][1], d0);
      if (hw < 2 || u < 4) mma16(d1, a[1], s[1][0], s[1][1], d1);
      mma16(d0, a[2], s[0][2], s[0][3], d0);
      if (hw < 2 || u < 4) mma16(d1, a[3], s[1][2], s[1][3], d1);
      wa += hw < 2 ? 4096 : 2048;
      sa += 64 + s1;
    }
    if (hw == 2) {
      d0[0] += d1[0];
      d0[2] += d1[2];
    }
    const float v = t & 2 ? (t & 1 ? d1[2] : d1[0]) : (t & 1 ? d0[2] : d0[0]);
    if (32 * hw + 8 * t < 80) st_rlx1(at<4>(box + M_LATE, 32 * hw + 8 * t + gq), tag(u32(v), ep));
  }
  if (b < N_FFN) {
    if (h == 0) mbar_expect_tx(bar + 8 * B_XS, 20480);
    bar_arrive<NB_LM, 128>();
  }
  wait_until(clock32() + LATE_GAP);
  {
    uint32_t v[4][4];
    const int q = 160 * which + (main20 || hw < 2 ? 20 * g + q4 : min(fin >> 2, 159));
    const uint4* src = at<16>(P.sc + M_LATE, q < 512 ? (q >> 4) * BOX + (q & 15) : ((q - 512) >> 2) * BOX + 16 + (q & 3));
#pragma unroll 1
    do {
#pragma unroll
      for (int i = 0; i < 4; ++i) ld_rlx4(v[i], src + i * 32 * BOX);
    } while (retry<1>(stale<4, 0>(v, ep) | stale<4, 1>(v, ep) | stale<4, 2>(v, ep) | stale<4, 3>(v, ep), budget));
    const uint32_t one = which == 2 ? 0x3F803F80u : 0u;
    uint32_t w[2], pw[2];
#pragma unroll
    for (int e = 0; e < 2; ++e) {
      w[e] = fma2(pack2(f32(v[0][2 * e]) + f32(v[1][2 * e]) + f32(v[2][2 * e]) + f32(v[3][2 * e]),
                        f32(v[0][2 * e + 1]) + f32(v[1][2 * e + 1]) + f32(v[2][2 * e + 1]) + f32(v[3][2 * e + 1])), 0x3F803F80u, one);
      pw[e] = fma2(w[e], wr[e], 0x80008000u);
    }
    const uint32_t dst = prm + (main20 || hw < 2 ? 160 * which + 8 * q4 : R_FIN + 4 * (lane & 6));
    sts2(dst, w[0], w[1]);
    sts2(dst + 800, pw[0], pw[1]);
    float s = main20 ? bf_lo(pw[0]) + bf_hi(pw[0]) + bf_lo(pw[1]) + bf_hi(pw[1]) : 0.f;
#pragma unroll
    for (int o = 16; o > 0; o >>= 1) s += shx(s, o);
    sts1(sb + OFF_KEY + 64 + 4 * hw, u32(s));
    mbar_arrive(bar + 8 * B_TAB);
    mbar_wait(bar + 8 * B_TAB, 1);
  }

  uint32_t ckey = 0;
  uint4* const odst = reinterpret_cast<uint4*>(P.out + (256 * j + rank) * 640 + 80 * g);
  if (hw == 0) {
    const uint32_t tile = min(4 * (lane & 3) + (lane >> 3), 9) * 16;
    uint32_t c1[4], sv[4], gb[4], x[4];
    ldsm4(c1, prm + R_C1 + tile);
    ldsm4(sv, prm + R_SB + tile);
    ldsm4(gb, prm + (lane & 4 ? R_GB + tile : R_ONE));
    const uint32_t bc = lds1(sb + OFF_KEY + 68), keep = lop3<0xF0>(gq & 4 ? ~0u : 0u, 0u, 0u);
    uint4* const cdst = at<16>(P.sc + M_CAND, (b - rank + (lane >> 4)) * BOX + 2 * (lane & 12) + 4 * rank + (lane & 3));
    uint32_t crow;
    {
      sched_fence(P.zero);
      bar_sync<NB_KEY, 288>();
      uint32_t k4[4];
      lds4(k4, sb + OFF_ROWS + 16 * lane);
      ckey = __reduce_max_sync(0xFFFFFFFFu, max(max(k4[0], k4[1]), max(k4[2], k4[3])));
      crow = (~ckey >> 1) & 127;
      const uint32_t nw = lds1(sb + OFF_ROWS + 512 + 4 * crow);
      ldsm4(x, sb + OFF_X2 + crow * 176 + tile);
      const uint32_t rs = dup_hi(nw), nm = dup_lo(nw);
#pragma unroll
      for (int e = 0; e < 4; ++e) x[e] = fma2(gb[e], fma2(fma2(x[e], rs, nm), c1[e], sv[e]), x[e] & keep);
      st_rlx4(cdst, tag(x[0], ep), x[1], gq == 2 ? ckey : x[2], gq == 2 ? bc : x[3]);
    }
    bar_arrive<NB_PUB, 288>();
    bar_sync<NB_OUT + 1, 160>();
    uint32_t next = clock32() + OUT_AT;
#pragma unroll 1
    for (int u = 0; u < 8; ++u) {
      if (u == 4) {
        bar_sync<NB_OUT, 160>();
        next = clock32();
      }
      wait_until(next);
      next += OUT_GAP;
      if (u != crow >> 4 && elect_one())
        asm volatile("cp.async.bulk.tensor.2d.global.shared::cta.bulk_group [%0, {%2, %3}], [%1];"
                     ::"l"(&P.om), "r"(sb + OFF_OUT + 2560 * u), "r"(640 * rank + 80 * g), "r"(128 * j + 16 * u) : "memory");
    }
    asm volatile("cp.async.bulk.commit_group;" ::: "memory");
  } else {
    if (b >= 80 || hw == 2) return;
    bar_sync<NB_WIN, 64>();
  }
  uint32_t m[7][4], wkey = lds1(sb + OFF_KEY + 80);
  if (b >= N_FFN) {
    gather<1, 0, 0>(m, at<64>(P.sc + M_CAND + 16, (lane & 14) * (2 * BOX) + (lane & 1)), ep, budget);
    wkey = __reduce_max_sync(0xFFFFFFFFu, m[0][2]);
  }
  const uint32_t wtok = ~wkey & 2047;
  if (hw == 0) {
    const uint32_t u = (~ckey >> 5) & 7, skip = ckey == wkey ? (~ckey >> 1) & 15 : 16;
#pragma unroll
    for (int i = 0; i < 5; ++i) {
      const uint32_t v = lane + 32 * i, r = (v * 205) >> 11;
      if (r != skip) *at<16>(odst, 2560 * u + v + 150 * r) = *reinterpret_cast<const uint4*>(sm + OFF_OUT + 2560 * u + 16 * v);
    }
    st_rlx1(at<4>(box + M_EPOCH, lane), ep);
    asm volatile("cp.async.bulk.wait_group.read 0;" ::: "memory");
    return;
  } else {
    const int cn = fin - 80 * fsl;
    gather<1, 0, 0>(m, at<16>(P.sc + M_CAND, (16 * (wtok >> 8) + (lane & 8 ? 2 * (lane & 7) : 2 * fsl + 1)) * BOX + 4 * (wtok & 1) +
                                             (lane & 8 ? 16 : 8 * (cn >> 5) + ((cn >> 1) & 3))), ep, budget);
    const uint32_t bw = cn & 16 ? (cn & 8 ? m[0][3] : m[0][2]) : (cn & 8 ? m[0][1] : m[0][0]);
    const uint32_t gw = lds1(prm + R_FIN + 4 * (lane & 6) + 4 * (b & 1));
    float r = f32(m[0][3]);
#pragma unroll
    for (int o = 1; o < 8; o <<= 1) r += shx(r, o);
    r = __shfl_sync(0xFFFFFFFFu, r, 8) + f32(wkey >> 31 ? wkey & 0x7FFFF800u : ~wkey | 0x7FFu);
    const float sg = bf_round(sigmoid(bf_round(r))), gv = lane & 1 ? bf_hi(gw) : bf_lo(gw), bv = lane & 1 ? bf_hi(bw) : bf_lo(bw);
    __nv_bfloat16* const dst = at<2>(P.out, wtok * 640 + fin);
    const uint4* const src = at<16>(P.sc + M_YP, (4 * (lane >> 3) + ((b >> 2) & 3)) * BOX + 32 * j + 8 * (b & 3) + (lane & 7));
    bar_sync<NB_YP, 64>();
    wait_until(clock32() + YP_GAP);
    gather_lazy<7, 16 * BOX, 32 * BOX, 0>(m, src, ep, budget, lane >= 24);
    float y[4];
#pragma unroll
    for (int e = 0; e < 4; ++e)
      y[e] = ((f32(m[0][e]) + f32(m[1][e])) + (f32(m[2][e]) + f32(m[3][e]))) + ((f32(m[4][e]) + f32(m[5][e])) + f32(m[6][e]));
    const bool u1 = lane & 2, u2 = lane & 4;
    const float e0 = (u1 ? y[1] : y[0]) + shx(u1 ? y[0] : y[1], 2), e1 = (u1 ? y[3] : y[2]) + shx(u1 ? y[2] : y[3], 2);
    float e = (u2 ? e1 : e0) + shx(u2 ? e0 : e1, 4);
    e += shx(e, 8);
    e += shx(e, 16);
    asm volatile("{.reg .pred p; setp.lt.u32 p, %2, 8; @p st.global.b16 [%0], %1;}"
                 ::"l"(dst), "h"((uint16_t)pack2(fmaf(gv, bf_round(bf_round(e) * sg), bv), 0.f)), "r"(lane) : "memory");
  }
}

template <int ODD> __device__ __forceinline__ uint32_t pack_acc(const float (&a)[96], const float (&b)[24], int part, int i, int h) {
  const int r = (i + 8 * ODD) % 10;
  const float* const v = r < 8 ? a + 32 * part + 4 * r : b + 8 * part + 4 * (r & 1);
  return pack2(v[2 * h], v[2 * h + 1]);
}
template <int V> struct Int { static constexpr int v = V; };
__device__ __forceinline__ constexpr int kpos(int i) { return i == 2 ? 8 : i == 7 ? 9 : i - (i > 2) - (i > 7); }

__device__ __forceinline__ void run_consumer(const Params& P, uint8_t* sm, uint32_t sb, int b, int warp, uint32_t ep, int budget) {
  const int tid = keep(threadIdx.x ^ 2), lane = tid & 31, gq = lane >> 2, t = lane & 3, p = warp >> 2, wq = warp & 3, rb = warp ^ 4;
  const int rank = b & 1, g = (b >> 1) & 7, j = b >> 4;
  const uint32_t bar = sb + OFF_BAR;
  uint4* const box = P.sc + b * BOX;
  const float z4[4] = {0.f, 0.f, 0.f, 0.f};

  uint32_t nrm[4];
  {
    uint32_t x[5][4], ones[10];
#pragma unroll
    for (int i = 0; i < 10; ++i) ones[i] = 0x3F803F80u;
    uint4* const dst = at<8>(box + M_ST1, tid >> 4);
    mbar_wait(bar + 8 * B_XS, 0);
    asm volatile("cp.async.wait_all;" ::: "memory");
#pragma unroll
    for (int i = 0; i < 5; ++i) lds4(x[i], sb + OFF_XS + 4096 * i + 16 * tid);
    float s[4], qlo, qhi, mean, rstd;
    row_stats(s, qlo, qhi, x, ones, gq);
    const float q = __shfl_sync(0xFFFFFFFFu, qlo + qhi, 4 * gq + (gq >> 1));
    float v = t & 1 ? q : s[0] + s[2];
    v += shx(v, 4);
    v += shx(v, 8);
    const uint32_t nw = norm_word(v, shx(v, 1), mean, rstd);
    if ((lane & 15) == 0) st_rlx2(dst, nw, ep);
    asm volatile("setmaxnreg.inc.sync.aligned.u32 224;");
  }

  float accA[96], accB[24];
#pragma unroll
  for (int i = 0; i < 96; ++i) asm volatile("" : "=f"(accA[i]));
#pragma unroll
  for (int i = 0; i < 24; ++i) asm volatile("" : "=f"(accB[i]));
  uint32_t xr[5][4];
#pragma unroll
  for (int i = 0; i < 20; ++i) asm volatile("" : "=r"(xr[i >> 2][i & 3]));
  const uint32_t turn = keep(NB_TURN + (tid >> 7)), pass = keep(NB_TURN + 1 - (tid >> 7));
  uint4* const opub = reinterpret_cast<uint4*>(__shfl_xor_sync(0xFFFFFFFFu, reinterpret_cast<uintptr_t>(at<16>(box + M_O, tid ^ 2)), 2));
  const uint4* src[7];
  const uint4* const lower = reinterpret_cast<const uint4*>(__shfl_xor_sync(0xFFFFFFFFu, reinterpret_cast<uintptr_t>(at<16>(P.sc + M_O, (b & ~14) * BOX + (tid ^ 2))), 2));
  const int l2 = lane ^ 2;
  const uint32_t ha = keep(sb + OFF_H + rb * 2560 + 16 * l2), lo = keep(sb + OFF_L + rb * 1280 + 16 * l2);
  const uint32_t va = keep(sb + OFF_H + 1280 + (rb + ((lane >> 3) & 1)) * 2560 + (lane >> 4) * 128 + (l2 & 7) * 16);
  const uint32_t M = keep((2 * (t ^ 2) > gq ? 0xFFFFu : 0u) | (2 * (t ^ 2) + 1 > gq ? 0xFFFF0000u : 0u)), gk = keep(g + (tid >> 9));
  {
    uint32_t la[4], raw[4][4], cw[4][4];
#pragma unroll
    for (int k = 0; k < 4; ++k) la[k] = keep(sb + (16 * rb + (l2 & 15)) * 128 + (((lane >> 4) ^ (l2 & 7) ^ (2 * k)) << 4));
    const uint32_t rel = keep(map_to_cta(bar + 8 * B_EMPTY, lane & 1)), c1a = keep(sb + OFF_C1 + 16 * (t ^ 2));
    const bool two = (ha & 0x1E0) == 0;
    constexpr uint64_t d0 = make_desc(SMEM_BASE + STAGE_A, 4096, 1024, 1), d1 = make_desc(SMEM_BASE + STAGE_A + STAGE_B0, 1024, 256, 3);
    const auto pick_x = [&](int st) {
#pragma unroll
      for (int k = 0; k < 4; ++k)
        if (g == (4 * st + k) / 5) ldsm4(xr[(4 * st + k) % 5], la[k] + (st & 3) * STAGE);
    };
    if (p == 1) turn_pass(pass);
    {
      const uint4* const src = at<8>(P.sc + M_ST1, (16 * j + 2 * rb) * 2 * BOX + 2 * gq + rank);
      mbar_wait(bar + 8 * B_FULL, 0);
#pragma unroll
      for (int k = 0; k < 4; ++k) ldsm4(raw[k], la[k]);
      pick_x(0);
      uint32_t n0[2], n1[2];
#pragma unroll 1
      do {
        ld_rlx2(n0, src);
        ld_rlx2(n1, src + BOX);
      } while (retry<~0u>(neq2(n0[1], n1[1], ep), budget));
      mbar_wait(bar + 8 * B_TAB, 0);
      if (warp == 0) bar_arrive<NB_GO, 160>();
#pragma unroll
      for (int k = 0; k < 4; ++k) lds4(cw[k], c1a + 64 * k);
      nrm[0] = dup_hi(n0[0]); nrm[1] = dup_hi(n1[0]); nrm[2] = dup_lo(n0[0]); nrm[3] = dup_lo(n1[0]);
    }
#pragma unroll
    for (int st = 0; st < 10; ++st) {
      uint32_t af[4][4];
      if (st) wg_wait();
      if (two) mbar_arrive_cluster(rel + 8 * ((st + 3) & 3));
#pragma unroll
      for (int k = 0; k < 16; ++k)
        af[k >> 2][k & 3] = fma2(fma2(raw[k >> 2][k & 3], nrm[k & 1], nrm[2 + (k & 1)]), cw[k >> 2][(k >> 1) & 1], cw[k >> 2][2 + ((k >> 1) & 1)]);
#pragma unroll
      for (int k = 0; k < 4; ++k)
        if (st < 9) lds4(cw[k], c1a + 256 * (st + 1) + 64 * k);
      wg_fence();
      turn_wait(turn);
#pragma unroll
      for (int q = 0; q < 8; ++q) {
        const int k = q >> 1;
        if (((q + 1) & 2) == 0) wgmma_n192(accA, af[k], d0 + ((st & 3) * STAGE + (k >> 1) * (STAGE_B0 / 2) + (k & 1) * 2048 >> 4), k + st);
        else wgmma_n48(accB, af[k], d1 + ((st & 3) * STAGE + (k >> 1) * (STAGE_B1 / 2) + (k & 1) * 512 >> 4), k + st);
        if (q == PASS1) turn_pass(pass);
      }
      wg_commit();
      if (st < 9) {
        mbar_wait(bar + 8 * ((st + 1) & 3), ((st + 1) >> 2) & 1);
#pragma unroll
        for (int k = 0; k < 4; ++k) ldsm4(raw[k], la[k] + ((st + 1) & 3) * STAGE);
        pick_x(st + 1);
      }
    }
    wg_wait();
    if (two) mbar_arrive_cluster(rel + 8);
  }

  uint32_t o[5][4];
  {
    uint32_t hi[20], vl[10], kl[10], kh[10], vv[20], qf[4][4], qs[4][2];
    const auto pack_hi = [&](auto odd) {
#pragma unroll
      for (int i = 0; i < 10; ++i) {
        hi[kpos(i)] = pack_acc<odd.v>(accA, accB, 1, i, 1);
        hi[10 + i] = pack_acc<odd.v>(accA, accB, 2, i, 1);
      }
    };
    const auto pack_rest = [&](auto odd) {
#pragma unroll
      for (int i = 0; i < 10; ++i) {
        kl[kpos(i)] = pack_acc<odd.v>(accA, accB, 1, i, 0);
        vl[i] = pack_acc<odd.v>(accA, accB, 2, i, 0);
      }
#pragma unroll
      for (int i = 0; i < 16; ++i) qf[i >> 2][i & 3] = pack_acc<odd.v>(accA, accB, 0, 5 * (i >> 3) + 3 * ((i >> 2) & 1) + ((i >> 1) & 1), i & 1);
#pragma unroll
      for (int i = 0; i < 4; ++i) qs[i | 1][i & 1] = pack_acc<odd.v>(accA, accB, 0, 5 * (i >> 1) + 2, i & 1);
    };
    const auto stage = [&]() {
#pragma unroll
      for (int q = 0; q < 5; ++q) stsm4(ha + 2560 + 512 * q, hi + 4 * q);
      stsm4(lo, vl);
      stsm4(lo + 512, vl + 4);
      stsm2(lo + 1024, vl + 8);
    };
    const auto pack_all = [&](auto odd) {
      pack_hi(odd);
#pragma unroll
      for (int q = 0; q < 5; ++q) hi[4 * q] = tag(hi[4 * q], ep);
      if (rb == 7) {
#pragma unroll
        for (int q = 0; q < 5; ++q) st_rlx4(opub + (M_HALO - M_O - 96 + 32 * q), hi + 4 * q);
      }
      sched_fence(P.zero);
      pack_rest(odd);
      stage();
    };
    if (g & 1) pack_all(Int<1>());
    else pack_all(Int<0>());
#pragma unroll
    for (int i = 0; i < 8; ++i) qs[i >> 1][i & 1] = (t >> 1) == ((i >> 1) & 1) ? qs[(i >> 1) | 1][i & 1] : 0u;
    __syncwarp();
    if (lane == 0) mbar_arrive(bar + 8 * B_HALO);
    float S0[4][4], S1[4][4], S2[4][4];
    ldsm4t(vl, lo);
    ldsm4t(vl + 4, lo + 512);
    ldsm2t(vl + 8, lo + 1024);
    sched_fence(P.zero);
#pragma unroll
    for (int hd = 0; hd < 4; ++hd) {
      mma16(S1[hd], qf[hd], kl[2 * hd], kl[2 * hd + 1], z4);
      mma16(S2[hd], qf[hd], hi[2 * hd], hi[2 * hd + 1], z4);
    }
#pragma unroll
    for (int hd = 0; hd < 4; ++hd) {
      mma8(S1[hd], qs[hd][0], qs[hd][1], kl[8 + (hd >> 1)], S1[hd]);
      mma8(S2[hd], qs[hd][0], qs[hd][1], hi[8 + (hd >> 1)], S2[hd]);
    }
    const bool up0 = M == ~0u, up1 = M != 0;
    uint32_t pp[4][2];
    const auto softmax = [&](const float (&A)[4][4], const float (&B)[4][4], int e) {
      const float SC = 0.22360679774997896f * 1.4426950408889634f;
      float a[4][2], mx[4];
#pragma unroll
      for (int hd = 0; hd < 4; ++hd) {
        a[hd][0] = up0 ? A[hd][2 * e] : B[hd][2 * e];
        a[hd][1] = up1 ? A[hd][2 * e + 1] : B[hd][2 * e + 1];
        mx[hd] = fmaxf(a[hd][0], a[hd][1]);
      }
#pragma unroll
      for (int s = 1; s < 4; s <<= 1) {
#pragma unroll
        for (int hd = 0; hd < 4; ++hd) mx[hd] = fmaxf(mx[hd], shx(mx[hd], s));
      }
#pragma unroll
      for (int hd = 0; hd < 4; ++hd) {
        const float ms = mx[hd] * -SC;
        pp[hd][e] = pack2(ex2(fmaf(a[hd][0], SC, ms)), ex2(fmaf(a[hd][1], SC, ms)));
      }
    };
#pragma unroll
    for (int i = 0; i < 7; ++i)
      asm volatile("{.reg .pred p; setp.gt.u32 p, %1, %2; selp.b64 %0, %3, %4, p;}" : "=l"(src[i]) : "r"(gk), "r"(i), "l"(lower), "l"(lower + 2 * BOX));
    mbar_wait(bar + 8 * B_HALO, 0);
    if (rb == 0) bar_sync<NB_HALO, 128>();
    ldsm4(kh, ha);
    ldsm4(kh + 4, ha + 512);
    ldsm2(kh + 8, ha + 1024);
#pragma unroll
    for (int i = 0; i < 5; ++i) ldsm4t(vv + 4 * i, va + 256 * i);
    const float ev = (j | rb) == 0 ? -1e9f / 0.22360679774997896f : 0.f, e4[4] = {ev, ev, ev, ev};
#pragma unroll
    for (int hd = 0; hd < 4; ++hd) mma16(S0[hd], qf[hd], kh[2 * hd], kh[2 * hd + 1], e4);
#pragma unroll
    for (int hd = 0; hd < 4; ++hd) mma8(S0[hd], qs[hd][0], qs[hd][1], kh[8 + (hd >> 1)], S0[hd]);
    softmax(S1, S2, 1);
    softmax(S0, S1, 0);
    float L[4][4], O[4][3][4];
#pragma unroll
    for (int hd = 0; hd < 4; ++hd) mma8(L[hd], pp[hd][0], pp[hd][1], 0x3F803F80u, z4);
#pragma unroll
    for (int hd = 0; hd < 4; ++hd) {
      const uint32_t p0 = pp[hd][0] & M, p2 = pp[hd][0] & ~M, p3 = pp[hd][1] & M, p5 = pp[hd][1] & ~M;
      const uint32_t z0 = pp[hd][0] & P.zero, z1 = pp[hd][1] & P.zero;
#pragma unroll
      for (int e = 0; e < 3; ++e) {
        const int f = 5 * (hd >> 1) + 2 * (hd & 1) + e;
        mma16(O[hd][e], p0, z0, z1, p5, vv[2 * f], vv[2 * f + 1], z4);
      }
#pragma unroll
      for (int e = 0; e < 3; ++e) mma8(O[hd][e], p2, p3, vl[5 * (hd >> 1) + 2 * (hd & 1) + e], O[hd][e]);
    }
    const bool odd = t >> 1;
#pragma unroll
    for (int hp = 0; hp < 2; ++hp) {
      const float (&A)[3][4] = O[2 * hp];
      const float (&B)[3][4] = O[2 * hp + 1];
#pragma unroll
      for (int e = 0; e < 2; ++e) {
        const float ra = rcp(L[2 * hp][2 * e]), rc = rcp(L[2 * hp + 1][2 * e]), rm = odd ? rc : ra;
        uint32_t* const d = &o[0][0] + 10 * hp + e;
        d[0] = pack2(A[0][2 * e] * ra, A[0][2 * e + 1] * ra);
        d[2] = pack2(A[1][2 * e] * ra, A[1][2 * e + 1] * ra);
        d[4] = pack2((odd ? B[0][2 * e] : A[2][2 * e]) * rm, (odd ? B[0][2 * e + 1] : A[2][2 * e + 1]) * rm);
        d[6] = pack2(B[1][2 * e] * rc, B[1][2 * e + 1] * rc);
        d[8] = pack2(B[2][2 * e] * rc, B[2][2 * e + 1] * rc);
      }
      if (hp == 0) {
#pragma unroll
        for (int s = 0; s < 2; ++s) {
          o[s][0] = tag(o[s][0], ep);
          st_rlx4(opub + 256 * s, o[s]);
        }
        sched_fence(P.zero);
        if (p == 1) bar_arrive<NB_PV, 256>();
      }
    }
#pragma unroll
    for (int s = 2; s < 5; ++s) o[s][0] = tag(o[s][0], ep);
  }

  float acc[40];
#pragma unroll
  for (int i = 0; i < 40; ++i) asm volatile("" : "=f"(acc[i]));
  uint32_t ga[10], pb[10], uw;
  uint4* const sdst = at<16>(box + M_ST2, 16 * rb + gq);
  const uint32_t prow = sb + OFF_PRM + (lane >> 3) * 16;
  {
    const uint64_t dw = make_desc(sb, 5120, 512, 2);
    uint32_t in[5][7][4];
    const auto fetch = [&](int s) {
#pragma unroll
      for (int i = 0; i < 7; ++i) ld_rlx4(in[s][i], src[i] + (2 * BOX * i + 256 * s));
    };
    st_rlx4(opub + 256 * 2, o[2]);
    mbar_wait(bar + 8 * B_WO0, 0);
    if (p == 0) bar_sync<NB_PV, 256>();
    fetch(0);
    wg_fence();
    turn_wait(turn);
#pragma unroll
    for (int s = 0; s < 5; ++s) {
      wgmma_n80(acc, o[s], dw + (wo_off(0) + 1024 * s >> 4), s);
      if (s == PASS0) turn_pass(pass);
    }
    wg_commit();
    mbar_wait(bar + 8 * B_WO1, 0);
    sched_fence(P.zero);
#pragma unroll 1
    while (retry<1>(stale<7, 0>(in[0], ep), budget)) {
#pragma unroll
      for (int i = 0; i < 7; ++i) ld_rlx4_stale(in[0][i], src[i] + 2 * BOX * i, in[0][i][0], ep);
    }
    fetch(1);
    st_rlx4(opub + 256 * 3, o[3]);
    st_rlx4(opub + 256 * 4, o[4]);
#pragma unroll
    for (int s = 0; s < 5; ++s) {
      if (s == FGO_STEP && tid == 128) mbar_arrive(bar + 8 * B_GO);
      wg_fence();
      turn_wait(turn);
#pragma unroll
      for (int i = 0; i < 7; ++i) {
        wgmma_n80(acc, in[s][i], dw + (wo_off(i + 1) + 1024 * s >> 4), 1);
        if (i == PASS_AT - 1) {
          if (s < 4 || p == 0) turn_pass(pass);
          if (s == 4) {
            wg_commit();
            wg_fence();
          }
          if (s + AHEAD > 1 && s + AHEAD < 5) {
            wg_commit();
            asm volatile("wgmma.wait_group.sync.aligned %0;" ::"n"(AHEAD == 1 ? 3 : 1) : "memory");
            fetch(s + AHEAD);
            wg_fence();
          }
        }
      }
      wg_commit();
    }
    sched_fence(P.zero);
    asm volatile("wgmma.wait_group.sync.aligned 2;" ::: "memory");
    mbar_wait(bar + 8 * B_TAB, 1);
    ld_row(ga, prow + R_GA);
    ldsm4(pb, lane & 1 ? prow + R_P : sb + OFF_PRM + R_ONE);
    ldsm4(pb + 4, lane & 1 ? prow + R_P + 64 : sb + OFF_PRM + R_ONE);
    ldsm2(pb + 8, lane & 1 ? prow + R_P + 128 : sb + OFF_PRM + R_ONE);
    uw = tag(lds1(sb + OFF_KEY + 64), ep);
    const uint32_t bad = stale<28, 0>(in[1], ep);
    uint32_t redo;
    asm volatile("{.reg .pred p; setp.ne.u32 p, %1, 0; barrier.cta.red.or.aligned.pred p, %2, 128, p; selp.u32 %0, 1, 0, p;}"
                 : "=r"(redo) : "r"(bad & 1u), "r"(turn + (NB_REDO - NB_TURN)) : "memory");
    if (redo) {
#pragma unroll 1
      for (int q = 0; q < 40; ++q) {
        const int i = q & 7, s = q >> 3;
        uint32_t a[1][4];
        wg_wait();
        gather<1, 0, 0>(a, lower + (2 * BOX * (i ? i - (i <= g) : g) + 256 * s), ep, budget);
        wg_fence();
        wgmma_n80(acc, a[0], dw + ((i < 4 ? 8 + i : i - 4) * WO + 1024 * s >> 4), q);
        wg_commit();
      }
    }
    wg_wait();
  }

  uint32_t c1[10], sv[10], gb[10], nw;
  const uint32_t trow = 16 * rb + (lane & 15), xt = sb + (lane >> 4) * 16;
  {
#pragma unroll
    for (int k = 0; k < 20; ++k) acc2(xr[k >> 2][k & 3], ga[k >> 1], pack2(acc[2 * k], acc[2 * k + 1]));
    float s[4], qlo, qhi;
    row_stats(s, qlo, qhi, xr, pb, gq);
    if (t == gq >> 1) {
      st_rlx4(sdst, u32(s[0]), u32(s[1]), u32(qlo), uw);
      st_rlx4(sdst + 8, u32(s[2]), u32(s[3]), u32(qhi), uw);
    }
    sched_fence(P.zero);
    const uint32_t tok = keep(256 * j + 32 * rb + (l2 & 30) + rank), kdst = keep(sb + OFF_ROWS + 64 * rb + 2 * (l2 & 30) + 512 * (lane & 1));
#pragma unroll
    for (int s5 = 0; s5 < 5; ++s5) stsm4(xt + trow * 176 + (OFF_X2 + 32 * s5), xr[s5]);
    uint32_t m[4][4];
    ld_row(c1, prow + R_C1);
    ld_row(sv, prow + R_SB);
    ld_row(gb, prow + R_GB);
    gather_lazy<4, 2 * BOX, 4 * BOX, 3>(m, at<16>(P.sc + M_ST2, (16 * j + rank + 8 * (lane & 1)) * BOX + 16 * rb + (lane >> 1)), ep, budget);
#pragma unroll
    for (int e = 0; e < 4; ++e) {
      s[e] = (f32(m[0][e]) + f32(m[1][e])) + (f32(m[2][e]) + f32(m[3][e]));
      s[e] += shx(s[e], 1);
    }
    float mean, rstd;
    nw = norm_word(s[0], s[2], mean, rstd);
    const uint32_t u = u32(rstd * fmaf(-mean, s[3], s[1]));
    const uint32_t key = ((u ^ ((uint32_t)((int)u >> 31) | 0x80000000u)) | 2047u) ^ tok;
    sts1(kdst, lane & 1 ? nw : key);
    bar_arrive<NB_KEY, 288>();
    bar_sync<NB_PUB, 288>();
  }

  if (p == 0 && b < N_FFN) {
    uint32_t wf[20][4], m[6][4];
    mbar_wait(bar + 8 * B_FFN, 1);
#pragma unroll
    for (int i = 0; i < 20; ++i)
      ldsm4t(wf[i], sb + OFF_FFN + (lane & 8) * 2560 + (80 * wq + 8 * (lane >> 4) + (lane & 7)) * 64 + (((i & 3) ^ ((lane >> 1) & 3)) << 4) + 1024 * (i >> 2));
    const uint32_t far = map_to_cta(sb, 0), dst = far + OFF_ACT + (4 * rank + wq) * 128 + gq * 16, step = map_to_cta(sb, 1) - far;
    gather_lazy<6, 64 * BOX, 8, 0>(m, at<16>(P.sc + M_CAND, (8 * (gq & 6) + 8 * rank + 2 * wq) * BOX + (lane & 7)), ep, budget);
    const bool second = m[5][2] > m[4][2];
    const uint32_t wtok = ~__reduce_max_sync(0xFFFFFFFFu, max(m[4][2], m[5][2]));
    float f[4][4];
#pragma unroll
    for (int s = 0; s < 5; ++s) {
      const uint32_t b0 = second ? m[(s & 6) + 1][2 * (s & 1)] : m[s & 6][2 * (s & 1)], b1 = second ? m[(s & 6) + 1][2 * (s & 1) + 1] : m[s & 6][2 * (s & 1) + 1];
#pragma unroll
      for (int mt = 0; mt < 4; ++mt) mma16(f[mt], wf[4 * s + mt], b0, b1, s ? f[mt] : z4);
    }
    if (t == ((wtok >> 8) & 3)) {
      const bool e = wtok & 1;
#pragma unroll
      for (int r = 0; r < 2; ++r)
        asm volatile("st.async.weak.shared::cluster.mbarrier::complete_tx::bytes.v4.f32 [%0], {%1, %2, %3, %4}, [%5];"
                     ::"r"(dst + r * step), "f"(e ? f[2 * r][1] : f[2 * r][0]), "f"(e ? f[2 * r][3] : f[2 * r][2]),
                       "f"(e ? f[2 * r + 1][1] : f[2 * r + 1][0]), "f"(e ? f[2 * r + 1][3] : f[2 * r + 1][2]), "r"(far + r * step + (OFF_BAR + 8 * B_ACT)) : "memory");
    }
    __syncwarp();
    if (warp == 0) {
      sts1(sb + OFF_KEY + 80, ~wtok);
      if (b < 80) bar_arrive<NB_WIN, 64>();
    }
  }
  {
    const uint32_t n0 = __shfl_sync(0xFFFFFFFFu, nw, 2 * gq), n1 = __shfl_sync(0xFFFFFFFFu, nw, 2 * gq + 16);
    nrm[0] = dup_hi(n0); nrm[1] = dup_hi(n1); nrm[2] = dup_lo(n0); nrm[3] = dup_lo(n1);
#pragma unroll
    for (int k = 0; k < 20; ++k) {
      uint32_t& x = xr[k >> 2][k & 3];
      acc2(x, gb[k >> 1], fma2(fma2(x, nrm[k & 1], nrm[2 + (k & 1)]), c1[k >> 1], sv[k >> 1]));
    }
  }
#pragma unroll
  for (int s5 = 0; s5 < 5; ++s5) stsm4(xt + trow * 160 + (OFF_OUT + 32 * s5), xr[s5]);
  asm volatile("fence.proxy.async.shared::cta;" ::: "memory");
  asm volatile("bar.arrive %0, 160;" ::"r"(turn + (NB_OUT - NB_TURN)) : "memory");
  if (p == 1 && b < N_FFN) {
    const uint32_t kr = ((lane & 7) >> 1) + 4 * (lane >> 4) + 8 * (lane & 1);
    uint32_t wd[10][4];
    mbar_wait(bar + 8 * B_XS, 0);
#pragma unroll
    for (int i = 0; i < 10; ++i) ldsm4t(wd[i], sb + OFF_FFN + 40960 + kr * 128 + (((2 * wq + ((lane >> 3) & 1)) ^ (kr & 7)) << 4) + 2048 * i);
    uint4* const ydst = at<16>(P.sc + M_YP, ((b & ~3) + wq) * BOX + 4 * (gq & 6) + 2 * (b & 3) + (gq & 1));
    mbar_wait(bar + 8 * B_ACT, 1);
    float v[8];
#pragma unroll
    for (int i = 0; i < 8; ++i) v[i] = f32(lds1(sb + OFF_ACT + 128 * i + 4 * lane));
    const float gu = bf_round(((v[0] + v[1]) + (v[2] + v[3])) + ((v[4] + v[5]) + (v[6] + v[7])));
    const float a = bf_round(gu * sigmoid(gu)) * shx(gu, 1);
    const uint32_t aw = pack2(a, shx(a, 2));
    const uint32_t b0 = __shfl_sync(0xFFFFFFFFu, aw, 4 * t), b1 = __shfl_sync(0xFFFFFFFFu, aw, 4 * t + 16);
    const bool odd = gq & 1;
    float y[5][4];
#pragma unroll
    for (int q = 0; q < 5; ++q) mma16(y[q], wd[2 * q], odd ? 0u : b0, odd ? 0u : b1, z4);
#pragma unroll
    for (int q = 0; q < 5; ++q) mma16(y[q], wd[2 * q + 1], odd ? b0 : 0u, odd ? b1 : 0u, y[q]);
    uint32_t w[4];
#pragma unroll
    for (int e = 0; e < 4; ++e) w[e] = u32(t & 2 ? (t & 1 ? y[3][e] : y[2][e]) : (t & 1 ? y[1][e] : y[0][e]));
    st_rlx4(ydst + 32 * t, tag(w[0], ep), w[1], w[2], w[3]);
    if (t == 0) st_rlx4(ydst + 128, tag(u32(y[4][0]), ep), u32(y[4][1]), u32(y[4][2]), u32(y[4][3]));
    __syncwarp();
    if (warp == 4 && b < 80) bar_arrive<NB_YP, 64>();
  }
}

template <bool BY_SM>
__global__ void __cluster_dims__(2, 1, 1) __launch_bounds__(384, 1) fused_block_kernel(const __grid_constant__ Params P) {
  extern __shared__ __align__(1024) uint8_t sm[];
  const uint32_t sb = (uint32_t)__cvta_generic_to_shared(sm), t0 = clock32();
  const int tid = threadIdx.x, lane = tid & 31;
  uint32_t key = blockIdx.x;
  if (BY_SM) asm("mov.u32 %0, %%smid;" : "=r"(key));
  const __nv_bfloat16* wmod = (&P.wmod)[tid >> 9];
  asm volatile("" : "+l"(wmod));
  const int warp = __shfl_sync(0xFFFFFFFFu, tid >> 5, 0), c = key >> 1, rank = blockIdx.x & 1;
  const uint32_t bar = sb + OFF_BAR;
  const auto role = [&]() {
    const int q7 = ((c - (BY_SM ? 32 : 36)) * 37) >> 8;
    if (BY_SM) return 2 * pick(c < 32, 8 * (c & 7) + (c >> 3), pick(c < 60, 8 * c - 55 * q7 - 244, c - 58)) + rank;
    return 2 * pick(c < 4, c, pick(c < 36, 4 + 4 * ((c - 4) & 7) + ((c - 4) >> 3), 4 * c - 27 * q7 - 108)) + rank;
  };
  const bool spare = BY_SM && (c >> 1) == 30;
  int budget = SPIN_LIMIT, b;
  uint32_t e0 = 0;
  if (warp == 11) {
    if (elect_one()) {
#pragma unroll
      for (int i = 0; i < 12; ++i) mbar_init(bar + 8 * i, i == B_TAB ? 96 : i == B_HALO ? 8 : (i >> 2) == 1 ? 16 : 1);
      asm volatile("fence.mbarrier_init.release.cluster;" ::: "memory");
    }
    __syncwarp();
    asm volatile("barrier.cluster.arrive.relaxed.aligned;" ::: "memory");
    b = role();
    if (spare) {
      wait_until(t0 + 4000);
      return;
    }
    const int g = (b >> 1) & 7;
    if (elect_one()) {
      mbar_expect_tx(bar + 8 * B_FULL, STAGE);
      tma2(sb, &P.xa, bar + 8 * B_FULL, 640 * rank, 128 * (b >> 4));
    }
    asm volatile("barrier.cluster.wait.aligned;" ::: "memory");
    if (elect_one()) {
      tma3_both(sb + STAGE_A + rank * (STAGE_B0 / 2), &P.w0, bar + 8 * B_FULL, 80 * g + 16 * (g & 1), 32 * rank, 0);
      tma3_both(sb + STAGE_A + STAGE_B0 + rank * (STAGE_B1 / 2), &P.w1, bar + 8 * B_FULL, 80 * g + 64 * (~g & 1), 32 * rank, 0);
    }
    st_rlx1(at<4>(P.sc + M_ST1, b * (4 * BOX) + lane), 0u);
    __syncwarp();
    if (lane == 0) mbar_arrive(bar + 8 * B_XS);
  } else {
    asm volatile("barrier.cluster.arrive.relaxed.aligned;" ::: "memory");
    const int u = (c & 48) + 2 * (c & 7) + ((c >> 3) & 1) - (c & 32 ? c & 7 : 0), kb = 2 * u + rank;
    const bool gemv = warp < 10 && c < 40;
    uint32_t cv = 0;
    if (gemv) {
      const __nv_bfloat16* src = at<16>(wmod, (320 * rank + (tid >> 2)) * 480 + 4 * u + (tid & 3));
      const uint32_t dst = sb + 3 * STAGE + 16 * (tid ^ ((tid >> 3) & 3));
#pragma unroll
      for (int i = 0; i < 4; ++i)
        asm volatile("cp.async.cg.shared.global.L2::128B [%0], [%1], 16;" ::"r"(dst + 5120 * i), "l"(src + i * 80 * 3840) : "memory");
    } else if (warp == 10 && elect_one()) {
      asm volatile("prefetch.tensormap [%0];" ::"l"(&P.xa) : "memory");
      asm volatile("prefetch.tensormap [%0];" ::"l"(&P.w0) : "memory");
      asm volatile("prefetch.tensormap [%0];" ::"l"(&P.w1) : "memory");
    }
    asm volatile("barrier.cluster.wait.aligned;" ::: "memory");
    if (spare) return;
    if (gemv) asm volatile("ld.global.nc.u16 %0, [%1];" : "=r"(cv) : "l"(at<2>(P.c, 320 * rank + 10 * (tid & 24) + ((tid >> 2) & ~7) + (tid & 7))));
    b = role();
    uint4* const box = P.sc + b * BOX;
    e0 = ld_rlx1(at<4>(box + M_EPOCH, lane));
    asm volatile("cp.async.commit_group;" ::: "memory");
    if (warp < 8) {
      const __nv_bfloat16* src = at<16>(P.x, (16 * b + (tid >> 4)) * 80 + (tid & 15));
      wait_until(t0 + XS_AT);
#pragma unroll
      for (int i = 0; i < 5; ++i)
        asm volatile("cp.async.cg.shared.global [%0], [%1], 16;" ::"r"(sb + OFF_XS + 4096 * i + 16 * tid), "l"(src + 128 * i) : "memory");
    }
    if (warp == 10) {
      uint4* const dst = at<16>(P.sc + TABLES, 80 * (lane & 28) + 4 * kb + (lane & 3));
      if (c < 40) st_rlx4(dst, 0u, 0u, 0u, 0u);
      if (lane == 0) mbar_expect_tx(bar + 8 * B_GO, c < 40 ? 1280 : 0);
      if (c < 40) {
        const uint32_t ep = next_epoch(e0);
        mbar_wait(bar + 8 * B_GO, 0);
        float v[10];
#pragma unroll
        for (int i = 0; i < 10; ++i) v[i] = f32(lds1(sb + OFF_RED + 128 * i + 4 * lane));
        float s = ((v[0] + v[1]) + (v[2] + v[3])) + ((v[4] + v[5]) + (v[6] + v[7])) + (v[8] + v[9]);
        s += shx(s, 16);
        const uint32_t w = fma2(pack2(s, shx(s, 1)), 0x3F803F80u, kb < 40 ? 0u : 0x3F803F80u);
        st_rlx4(dst, __shfl_sync(0xFFFFFFFFu, w, 2 * (lane & 3)), __shfl_sync(0xFFFFFFFFu, w, 2 * (lane & 3) + 8), ep, ep);
      }
    } else if (gemv) {
      const float x = bf_lo(cv), s = x * sigmoid(x);
      const uint32_t sw = pack2(s, shx(s, 1));
      uint32_t bw[4], a[4][4];
#pragma unroll
      for (int i = 0; i < 4; ++i) bw[i] = __shfl_sync(0xFFFFFFFFu, sw, 8 * i + 2 * (lane & 3));
      const uint32_t far = map_to_cta(sb, (lane >> 1) & 1), dst = far + OFF_RED + 128 * warp + 64 * rank + 32 * (lane & 1) + (lane & 28);
      const uint32_t la = sb + 3 * STAGE + 512 * warp + (lane >> 4) * 5120 + (lane & 7) * 64 + ((((lane >> 3) & 1) ^ ((lane >> 1) & 3)) << 4);
      sched_fence(P.zero);
      asm volatile("cp.async.wait_group 0;" ::: "memory");
      __syncwarp();
#pragma unroll
      for (int i = 0; i < 4; ++i) ldsm4t(a[i], (la ^ (32 * (i & 1))) + (i >> 1) * 10240);
      float d[2][4];
      const float z4[4] = {0.f, 0.f, 0.f, 0.f};
#pragma unroll
      for (int i = 0; i < 4; ++i) mma16(d[i & 1], a[i], bw[i & 2], bw[(i & 2) + 1], i < 2 ? z4 : d[i & 1]);
      const float v = lane & 2 ? (lane & 1 ? d[1][2] : d[1][0]) : (lane & 1 ? d[0][2] : d[0][0]);
      asm volatile("st.async.weak.shared::cluster.mbarrier::complete_tx::bytes.f32 [%0], %1, [%2];" ::"r"(dst), "f"(v), "r"(far + OFF_BAR + 8 * B_GO) : "memory");
    }
  }
  if (warp >= 8) {
    asm volatile("setmaxnreg.dec.sync.aligned.u32 56;");
    if (warp == 11) {
      wait_until(t0 + S_GAP);
      run_producer(P, sm, sb, b, t0);
    } else {
      run_helper(P, sm, sb, b, warp - 8, next_epoch(e0), budget, t0 + POLL_AT);
    }
  } else {
    run_consumer(P, sm, sb, b, warp, next_epoch(e0), budget);
  }
}

typedef CUresult (*EncodeFn)(CUtensorMap*, CUtensorMapDataType, cuuint32_t, void*, const cuuint64_t*, const cuuint64_t*, const cuuint32_t*,
                             const cuuint32_t*, CUtensorMapInterleave, CUtensorMapSwizzle, CUtensorMapL2promotion, CUtensorMapFloatOOBfill);

void encode(EncodeFn fn, CUtensorMap* m, const void* base, int rank, const cuuint64_t* dims, const cuuint64_t* strides, const cuuint32_t* box,
            CUtensorMapSwizzle sw) {
  const cuuint32_t es[3] = {1, 1, 1};
  fn(m, CU_TENSOR_MAP_DATA_TYPE_BFLOAT16, rank, const_cast<void*>(base), dims, strides, box, es, CU_TENSOR_MAP_INTERLEAVE_NONE, sw,
     CU_TENSOR_MAP_L2_PROMOTION_L2_128B, CU_TENSOR_MAP_FLOAT_OOB_FILL_NONE);
}

}

extern "C" void kernel_launch(void* const* d_in, const int* in_sizes, int n_in, void* d_out, int out_size) {
  (void)in_sizes; (void)n_in; (void)out_size;
  static EncodeFn fn = nullptr;
  static void* scratch = nullptr;
  static bool by_sm = false;
  if (!fn) {
    void* f = nullptr;
    cudaDriverEntryPointQueryResult q;
    cudaGetDriverEntryPoint("cuTensorMapEncodeTiled", &f, cudaEnableDefault, &q);
    fn = (EncodeFn)f;
    cudaFuncSetAttribute(fused_block_kernel<true>, cudaFuncAttributeMaxDynamicSharedMemorySize, SMEM_BYTES);
    cudaFuncSetAttribute(fused_block_kernel<false>, cudaFuncAttributeMaxDynamicSharedMemorySize, SMEM_BYTES);
    int dev = 0, sms = 0, pairs = 0;
    cudaGetDevice(&dev);
    cudaDeviceGetAttribute(&sms, cudaDevAttrMultiProcessorCount, dev);
    cudaLaunchConfig_t cfg = {};
    cudaLaunchAttribute at;
    at.id = cudaLaunchAttributeClusterDimension;
    at.val.clusterDim.x = 2;
    at.val.clusterDim.y = at.val.clusterDim.z = 1;
    cfg.gridDim = dim3(132);
    cfg.blockDim = dim3(384);
    cfg.dynamicSmemBytes = SMEM_BYTES;
    cfg.attrs = &at;
    cfg.numAttrs = 1;
    cudaOccupancyMaxActiveClusters(&pairs, fused_block_kernel<true>, &cfg);
    by_sm = sms == 132 && pairs == 66;
    cudaGetSymbolAddress(&scratch, g_scratch);
  }
  Params P;
  P.sc = (uint4*)scratch;
  P.zero = 0;
  const cuuint64_t xd[2] = {1280, 1024}, xs[1] = {2560};
  const cuuint32_t xb[2] = {64, 128};
  encode(fn, &P.xa, d_in[0], 2, xd, xs, xb, CU_TENSOR_MAP_SWIZZLE_128B);
  const cuuint32_t ob[2] = {80, 16};
  encode(fn, &P.om, d_out, 2, xd, xs, ob, CU_TENSOR_MAP_SWIZZLE_NONE);
  const cuuint64_t wd3[3] = {640, 640, 3}, ws3[2] = {3840, 1280};
  const cuuint32_t w0b[3] = {64, 32, 3}, w1b[3] = {16, 32, 3};
  encode(fn, &P.w0, d_in[1], 3, wd3, ws3, w0b, CU_TENSOR_MAP_SWIZZLE_128B);
  encode(fn, &P.w1, d_in[1], 3, wd3, ws3, w1b, CU_TENSOR_MAP_SWIZZLE_32B);
  const cuuint64_t md[2] = {3840, 640}, ms[1] = {7680};
  const cuuint32_t mb0[2] = {64, 160}, mb1[2] = {16, 160};
  encode(fn, &P.wm0, d_in[9], 2, md, ms, mb0, CU_TENSOR_MAP_SWIZZLE_128B);
  encode(fn, &P.wm1, d_in[9], 2, md, ms, mb1, CU_TENSOR_MAP_SWIZZLE_32B);
  const cuuint64_t od3[3] = {608, 640, 2}, os3[2] = {1280, 64}, od2[2] = {640, 640}, os2[1] = {1280};
  const cuuint32_t oab[3] = {32, 80, 2}, obb[2] = {16, 80};
  encode(fn, &P.woa, d_in[2], 3, od3, os3, oab, CU_TENSOR_MAP_SWIZZLE_64B);
  encode(fn, &P.wob, d_in[2], 2, od2, os2, obb, CU_TENSOR_MAP_SWIZZLE_64B);
  const cuuint64_t gd[3] = {1728, 160, 4}, gs[2] = {3456, 160 * 3456}, dd[3] = {64, 1728, 10}, ds[2] = {1280, 128};
  const cuuint32_t gb[3] = {32, 160, 1}, db[3] = {64, 16, 5};
  encode(fn, &P.wg, d_in[5], 3, gd, gs, gb, CU_TENSOR_MAP_SWIZZLE_64B);
  encode(fn, &P.wu, d_in[6], 3, gd, gs, gb, CU_TENSOR_MAP_SWIZZLE_64B);
  encode(fn, &P.wd, d_in[7], 3, dd, ds, db, CU_TENSOR_MAP_SWIZZLE_128B);
  P.x = (const __nv_bfloat16*)d_in[0];
  P.wqkv = (const __nv_bfloat16*)d_in[1];
  P.wr = (const __nv_bfloat16*)d_in[4];
  P.wo = (const __nv_bfloat16*)d_in[2];
  P.wgate = (const __nv_bfloat16*)d_in[5];
  P.wup = (const __nv_bfloat16*)d_in[6];
  P.wdown = (const __nv_bfloat16*)d_in[7];
  P.c = (const __nv_bfloat16*)d_in[8];
  P.wmod = (const __nv_bfloat16*)d_in[9];
  P.out = (__nv_bfloat16*)d_out;
  if (by_sm) fused_block_kernel<true><<<132, 384, SMEM_BYTES>>>(P);
  else fused_block_kernel<false><<<128, 384, SMEM_BYTES>>>(P);
}
```
